```python
import torch

def _softmax(x, axis=-1):
    return torch.softmax(x, dim=axis)
def _gelu(x):
    return torch.nn.functional.gelu(x, approximate="tanh")
def _silu(x):
    return torch.nn.functional.silu(x)
def _sigmoid(x):
    return torch.sigmoid(x)
def _layernorm(x, axis=-1, eps=1e-5):
    m = x.mean(dim=axis, keepdim=True)
    v = x.var(dim=axis, keepdim=True, unbiased=False)
    return (x - m) / torch.sqrt(v + eps)
def _scatter_add(tgt, idx, src, axis=0):
    return tgt.clone().index_add_(axis, idx, src)
def _segment_sum(src, seg, n):
    out = torch.zeros((n,) + src.shape[1:], dtype=src.dtype)
    return out.index_add_(0, seg, src)
def _pad(x, pw):
    flat = tuple(v for pair in reversed(pw) for v in pair)
    return torch.nn.functional.pad(x, flat)

kernel_name = 'gated_mix__sliding_block_cached__dense_activation_squared_relu__decode'

def setup_inputs():

    _w = (lambda a: (lambda t: t.to(torch.bfloat16) if t.is_floating_point() else t)(torch.as_tensor(a)))
    def _A_setup():
        B, Sq, D = 2, 1, 576
        Hq, Hkv, Sk, Dh = 32, 16, 32768, 128
        assert Hq % Hkv == 0, (Hq, Hkv)
        return {
            "x": _w((lambda *s: torch.randn(*s, dtype=torch.bfloat16) * 0.05)(B, Sq, D)),
            "k_cache": _w((lambda *s: torch.randn(*s, dtype=torch.bfloat16) * 6.4)(B, Hkv, Sk, Dh)),
            "v_cache": _w((lambda *s: torch.randn(*s, dtype=torch.bfloat16) * 0.4)(B, Hkv, Sk, Dh)),
            "wq": _w((lambda *s: torch.randn(*s, dtype=torch.bfloat16) * 6.4)(D, Hq * Dh) * (D ** -0.5)),
            "wo": _w((lambda *s: torch.randn(*s, dtype=torch.bfloat16) * 0.4)(Hq * Dh, D) * ((Hq * Dh) ** -0.5)),
        }
    _A_in = _A_setup()

    def _B_setup():
        B, S, D, F = 2, 1, 576, 4608
        return {
            "x": _w((lambda *s: torch.randn(*s, dtype=torch.bfloat16) * 0.05)(B, S, D)),
            "w1": _w((lambda *s: torch.randn(*s, dtype=torch.bfloat16) * 0.05)(D, F)),
            "b1": _w((lambda *s: torch.randn(*s, dtype=torch.bfloat16) * 0.05)(F)),
            "w2": _w((lambda *s: torch.randn(*s, dtype=torch.bfloat16) * 0.05)(F, D)),
            "b2": _w((lambda *s: torch.randn(*s, dtype=torch.bfloat16) * 0.05)(D)),
        }
    _B_in = _B_setup()

    return {
        "A_x": _A_in["x"],
        "A_k_cache": _A_in["k_cache"],
        "A_v_cache": _A_in["v_cache"],
        "A_wq": _A_in["wq"],
        "A_wo": _A_in["wo"],
        "B_x": _B_in["x"],
        "B_w1": _B_in["w1"],
        "B_b1": _B_in["b1"],
        "B_w2": _B_in["w2"],
        "B_b2": _B_in["b2"],
        "gate_w": _w((lambda *s: torch.randn(*s, dtype=torch.bfloat16) * 0.05)(576) * 16.0),
    }

def reference(A_x, A_k_cache, A_v_cache, A_wq, A_wo, B_x, B_w1, B_b1, B_w2, B_b2, gate_w):
    def _A_ref(x, k_cache, v_cache, wq, wo):
        B, Sq, D = x.shape
        Hq, Dh = 32, 128
        Hkv, Sk = k_cache.shape[1], k_cache.shape[2]
        W = min(4096, max(256, Sk // 4))
        rep = Hq // Hkv
        q = (lambda x, *d: x.permute(*d))((x @ wq).reshape(B, Sq, Hq, Dh), 0, 2, 1, 3)
        k = (lambda x, n, axis: torch.repeat_interleave(x, n, dim=axis))(k_cache[:, :, Sk - W:, :], rep, axis=1)
        v = (lambda x, n, axis: torch.repeat_interleave(x, n, dim=axis))(v_cache[:, :, Sk - W:, :], rep, axis=1)
        scores = torch.einsum("bhqd,bhkd->bhqk", q, k) * (Dh ** -0.5)
        p = _softmax(scores, axis=-1)
        o = torch.einsum("bhqk,bhkd->bhqd", p, v)
        return (lambda x, *d: x.permute(*d))(o, 0, 2, 1, 3).reshape(B, Sq, Hq * Dh) @ wo

    def _B_ref(x, w1, b1, w2, b2):
        h = torch.einsum("bsd,df->bsf", x, w1) + b1
        zero = torch.zeros_like(h)
        r = torch.where(h > zero, h, zero)
        h = r * r
        out = torch.einsum("bsf,fd->bsd", h, w2) + b2
        return out

    x = A_x
    g = _sigmoid((x * gate_w).sum(-1, keepdims=True))
    a = _A_ref(x, A_k_cache, A_v_cache, A_wq, A_wo)
    b = _B_ref(x, B_w1, B_b1, B_w2, B_b2)
    return g * a + (1 - g) * b
```

```cpp
#include <cuda_runtime.h>
#include <cuda_bf16.h>
#include <cuda.h>
#include <stdint.h>

namespace {

constexpr int D_MODEL = 576;
constexpr int SK = 32768;
constexpr int WIN = 4096;
constexpr int NCTA = 128;
constexpr int NRED = 72;
constexpr int SLOT = 16384;
#define NST 12
#define INFL 8
#define INFL0 5
constexpr int I_KV = 3, I_W1 = 35, I_W2 = 38, I_WO = 41, NITEM = 44;
constexpr int SPIN_LIMIT = 1 << 17;

__device__ unsigned g_epoch;
__device__ __align__(128) float g_q[2 * 4096];
__device__ __align__(128) float g_o[128 * 8 * 40];
__device__ __align__(128) float g_fin[NRED * NCTA * 16];
#define TS(i) do {} while (0)

struct __align__(16) Smem {
    uint64_t full[NST + 9];
    uint64_t empty[NST];
    uint64_t qbar, obar;
    float red[4][2][48];
    float ocomb[4][2][128];
    float ml[4][2][2];
    float obuf[8][40];
    float fin[2][4][16];
    uint32_t qs[2][64];
    uint32_t hs[2][24];
};

__device__ __forceinline__ uint32_t s2u(const void* p) { return (uint32_t)__cvta_generic_to_shared(p); }
__device__ __forceinline__ void mbar_init(uint32_t a, int c) { asm volatile("mbarrier.init.shared.b64 [%0], %1;" ::"r"(a), "r"(c) : "memory"); }
__device__ __forceinline__ void mbar_expect(uint32_t a, uint32_t b) { asm volatile("mbarrier.arrive.expect_tx.shared.b64 _, [%0], %1;" ::"r"(a), "r"(b) : "memory"); }
__device__ __forceinline__ void mbar_arrive(uint32_t a) { asm volatile("mbarrier.arrive.shared.b64 _, [%0];" ::"r"(a) : "memory"); }
__device__ __forceinline__ void mbar_wait(uint32_t a, uint32_t ph) {
    uint32_t ok;
    int it = 0;
    do {
        asm volatile("{\n.reg .pred p;\nmbarrier.try_wait.parity.shared.b64 p, [%1], %2;\nselp.u32 %0, 1, 0, p;\n}" : "=r"(ok) : "r"(a), "r"(ph) : "memory");
    } while (!ok && ++it < SPIN_LIMIT);
}
__device__ __forceinline__ void mbar_wait_cluster(uint32_t a) {
    uint32_t ok;
    int it = 0;
    do {
        asm volatile("{\n.reg .pred p;\nmbarrier.try_wait.parity.acquire.cluster.shared::cta.b64 p, [%1], 0;\nselp.u32 %0, 1, 0, p;\n}" : "=r"(ok) : "r"(a) : "memory");
    } while (!ok && ++it < SPIN_LIMIT);
}
__device__ __forceinline__ uint32_t mapa(uint32_t a, uint32_t rank) {
    uint32_t r;
    asm("mapa.shared::cluster.u32 %0, %1, %2;" : "=r"(r) : "r"(a), "r"(rank));
    return r;
}
__device__ __forceinline__ void st_async1(uint32_t a, uint32_t v, uint32_t bar) {
    asm volatile("st.async.shared::cluster.mbarrier::complete_tx::bytes.u32 [%0], %1, [%2];" ::"r"(a), "r"(v), "r"(bar) : "memory");
}
__device__ __forceinline__ void st_async2(uint32_t a, float v0, float v1, uint32_t bar) {
    asm volatile("st.async.shared::cluster.mbarrier::complete_tx::bytes.v2.f32 [%0], {%1,%2}, [%3];" ::"r"(a), "f"(v0), "f"(v1), "r"(bar) : "memory");
}
__device__ __forceinline__ void tma2d(uint32_t dst, const CUtensorMap* m, int c0, int c1, uint32_t bar) {
    asm volatile("cp.async.bulk.tensor.2d.shared::cluster.global.mbarrier::complete_tx::bytes [%0], [%1, {%3, %4}], [%2];" ::"r"(dst), "l"(m), "r"(bar), "r"(c0), "r"(c1) : "memory");
}
__device__ __forceinline__ void tma3d(uint32_t dst, const CUtensorMap* m, int c0, int c1, int c2, uint32_t bar) {
    asm volatile("cp.async.bulk.tensor.3d.shared::cluster.global.mbarrier::complete_tx::bytes [%0], [%1, {%3, %4, %5}], [%2];" ::"r"(dst), "l"(m), "r"(bar), "r"(c0), "r"(c1), "r"(c2) : "memory");
}
__device__ __forceinline__ void ldsm4(uint32_t* r, uint32_t a) {
    asm volatile("ldmatrix.sync.aligned.m8n8.x4.shared.b16 {%0,%1,%2,%3}, [%4];" : "=r"(r[0]), "=r"(r[1]), "=r"(r[2]), "=r"(r[3]) : "r"(a) : "memory");
}
__device__ __forceinline__ void ldsm4t(uint32_t* r, uint32_t a) {
    asm volatile("ldmatrix.sync.aligned.m8n8.x4.trans.shared.b16 {%0,%1,%2,%3}, [%4];" : "=r"(r[0]), "=r"(r[1]), "=r"(r[2]), "=r"(r[3]) : "r"(a) : "memory");
}
__device__ __forceinline__ void mma(float* c, uint32_t a0, uint32_t a1, uint32_t a2, uint32_t a3, uint32_t b0, uint32_t b1) {
    asm volatile("mma.sync.aligned.m16n8k16.row.col.f32.bf16.bf16.f32 {%0,%1,%2,%3}, {%4,%5,%6,%7}, {%8,%9}, {%0,%1,%2,%3};"
                 : "+f"(c[0]), "+f"(c[1]), "+f"(c[2]), "+f"(c[3]) : "r"(a0), "r"(a1), "r"(a2), "r"(a3), "r"(b0), "r"(b1));
}
__device__ __forceinline__ uint32_t pack_bf16(float lo, float hi) {
    uint32_t r;
    asm("cvt.rn.bf16x2.f32 %0, %1, %2;" : "=r"(r) : "f"(hi), "f"(lo));
    return r;
}
__device__ __forceinline__ float bf_lo(uint32_t v) { return __uint_as_float(v << 16); }
__device__ __forceinline__ float bf_hi(uint32_t v) { return __uint_as_float(v & 0xffff0000u); }
__device__ __forceinline__ float bf_round(float v) { return __bfloat162float(__float2bfloat16_rn(v)); }
__device__ __forceinline__ float ex2(float v) { float r; asm("ex2.approx.ftz.f32 %0, %1;" : "=f"(r) : "f"(v)); return r; }
__device__ __forceinline__ float rcp(float v) { float r; asm("rcp.approx.ftz.f32 %0, %1;" : "=f"(r) : "f"(v)); return r; }
__device__ __forceinline__ uint32_t ldg32(const void* p) {
    uint32_t v;
    asm volatile("ld.global.nc.u32 %0, [%1];" : "=r"(v) : "l"(p));
    return v;
}
__device__ __forceinline__ uint32_t ldg16(const void* p) {
    uint16_t v;
    asm volatile("ld.global.nc.u16 %0, [%1];" : "=h"(v) : "l"(p));
    return v;
}
__device__ __forceinline__ uint32_t tagw(float v, uint32_t tag) { return (__float_as_uint(v) & ~3u) | tag; }
__device__ __forceinline__ void st_msg2(float* p, float a, float b, uint32_t tag) {
    asm volatile("st.volatile.global.v2.u32 [%0], {%1,%2};" ::"l"(p), "r"(tagw(a, tag)), "r"(tagw(b, tag)) : "memory");
}
__device__ __forceinline__ uint2 ld_msg2(const float* p) {
    uint2 v;
    asm volatile("ld.volatile.global.v2.u32 {%0,%1}, [%2];" : "=r"(v.x), "=r"(v.y) : "l"(p) : "memory");
    return v;
}
__device__ __forceinline__ void ld_msg4_if(uint4& v, const float* p, bool pred) {
    asm volatile("{\n.reg .pred p;\nsetp.ne.u32 p, %5, 0;\n@p ld.volatile.global.v4.u32 {%0,%1,%2,%3}, [%4];\n}"
                 : "+r"(v.x), "+r"(v.y), "+r"(v.z), "+r"(v.w) : "l"(p), "r"((uint32_t)pred) : "memory");
}
__device__ __forceinline__ bool ok2(uint2 v, uint32_t tag) { return (((v.x ^ tag) | (v.y ^ tag)) & 3u) == 0; }
__device__ __forceinline__ bool ok4(uint4 v, uint32_t tag) { return (((v.x ^ tag) | (v.y ^ tag) | (v.z ^ tag) | (v.w ^ tag)) & 3u) == 0; }
__device__ __forceinline__ void bar_sync(int id, int n) { asm volatile("bar.sync %0, %1;" ::"r"(id), "r"(n) : "memory"); }
__device__ __forceinline__ bool bar_and(int id, int n, bool v) {
    uint32_t r;
    asm volatile("{\n.reg .pred p, q;\nsetp.ne.u32 p, %3, 0;\nbar.red.and.pred q, %1, %2, p;\nselp.u32 %0, 1, 0, q;\n}" : "=r"(r) : "r"(id), "r"(n), "r"((uint32_t)v) : "memory");
    return r;
}

__device__ __forceinline__ uint32_t full_bar(Smem& sm, int i) { return s2u(&sm.full[i < I_W1 ? i % NST : NST + i - I_W1]); }
__device__ __forceinline__ void wait_full(Smem& sm, int i) { mbar_wait(full_bar(sm, i), i < I_W1 ? (i / NST) & 1 : 0); }
__device__ __forceinline__ void release(Smem& sm, int i) { mbar_arrive(s2u(&sm.empty[i % NST])); }

__device__ __forceinline__ void gate(const uint32_t* gx, float& g0, float& g1) {
    float s0 = 0.f, s1 = 0.f;
#pragma unroll
    for (int i = 0; i < 9; i++) {
        s0 = fmaf(bf_lo(gx[i]), bf_lo(gx[9 + i]), fmaf(bf_hi(gx[i]), bf_hi(gx[9 + i]), s0));
        s1 = fmaf(bf_lo(gx[i]), bf_lo(gx[18 + i]), fmaf(bf_hi(gx[i]), bf_hi(gx[18 + i]), s1));
    }
#pragma unroll
    for (int o = 16; o; o >>= 1) { s0 += __shfl_xor_sync(~0u, s0, o); s1 += __shfl_xor_sync(~0u, s1, o); }
    g0 = 1.f / (1.f + __expf(-s0));
    g1 = 1.f / (1.f + __expf(-s1));
}

template <bool CL>
__global__ void __launch_bounds__(288, 1)
fused_kernel(const __grid_constant__ CUtensorMap mK, const __grid_constant__ CUtensorMap mV,
             const __grid_constant__ CUtensorMap mWq, const __grid_constant__ CUtensorMap mW1,
             const __grid_constant__ CUtensorMap mW2, const __grid_constant__ CUtensorMap mWo,
             const __nv_bfloat16* __restrict__ x, const __nv_bfloat16* __restrict__ b1,
             const __nv_bfloat16* __restrict__ b2, const __nv_bfloat16* __restrict__ gate_w,
             __nv_bfloat16* __restrict__ out) {
    extern __shared__ __align__(1024) unsigned char smem_raw[];
    __shared__ Smem sm;
    const uint32_t ring = (s2u(smem_raw) + 1023u) & ~1023u;
    const int tid = threadIdx.x, warp = tid >> 5, lane = tid & 31;
    const int c = blockIdx.x;

    const int kvrow = ((((c >> 2) & 1) * 16 + (c >> 3)) * SK) + (SK - WIN) + (c & 3) * 1024;
    auto issue = [&](int i) {
        const uint32_t dst = ring + (i % NST) * SLOT, bar = full_bar(sm, i);
        if (i < I_KV) {
            mbar_expect(bar, 192 * 64);
            tma2d(dst, &mWq, c * 32, i * 192, bar);
        } else if (i < I_W1) {
            mbar_expect(bar, 16384);
            tma3d(dst, ((i - I_KV) & 1) ? &mV : &mK, 0, kvrow + ((i - I_KV) >> 1) * 64, 0, bar);
        } else if (i < I_W2) {
            mbar_expect(bar, 192 * 80);
            tma2d(dst, &mW1, (c * 36) & ~7, (i - I_W1) * 192, bar);
        } else if (i < I_WO) {
            mbar_expect(bar, 36 * 384);
            tma3d(dst, &mW2, 0, c * 36, (i - I_W2) * 3, bar);
        } else {
            mbar_expect(bar, 32 * 384);
            tma3d(dst, &mWo, 0, c * 32, (i - I_WO) * 3, bar);
        }
    };
    if (tid == 256) {
        TS(0);
#pragma unroll
        for (int i = 0; i < INFL0; i++) mbar_init(s2u(&sm.full[i]), 1);
        asm volatile("fence.proxy.async.shared::cta;" ::: "memory");
#pragma unroll
        for (int i = 0; i < INFL0; i++) issue(i);
        TS(11);
    } else if (lane == 0 && warp < 4) {
        for (int i = INFL0 + warp; i < NST + 9; i += 4) mbar_init(s2u(&sm.full[i]), 1);
        for (int i = warp; i < NST; i += 4) mbar_init(s2u(&sm.empty[i]), 4);
        if (warp == 3) {
            mbar_init(s2u(&sm.qbar), 1);
            mbar_init(s2u(&sm.obar), CL ? 1 : 128);
            if (CL) { mbar_expect(s2u(&sm.qbar), 512); mbar_expect(s2u(&sm.obar), 8 * 136); }
        }
        asm volatile("fence.mbarrier_init.release.cluster;" ::: "memory");
        asm volatile("fence.proxy.async.shared::cta;" ::: "memory");
    }
    const uint32_t* x32 = reinterpret_cast<const uint32_t*>(x);
    uint32_t xf[18], gx[27], epoch = 0, bias_raw = 0;
    if (warp < 8) {
        if (warp >= 4) {
            const uint32_t* xp = x32 + ((lane >> 2) & 1) * 288 + (warp - 4) * 24 + (lane & 3);
#pragma unroll
            for (int j = 0; j < 3; j++)
#pragma unroll
                for (int i = 0; i < 3; i++) { xf[(j * 3 + i) * 2] = ldg32(xp + j * 96 + i * 8); xf[(j * 3 + i) * 2 + 1] = ldg32(xp + j * 96 + i * 8 + 4); }
            const int k = (tid - 128) % 48;
            if (k < 36) bias_raw = ldg16(b1 + c * 36 + k);
        } else if (c < NRED && tid < 16) {
            bias_raw = ldg16(b2 + c * 8 + (tid >> 1));
        }
        asm volatile("ld.volatile.global.u32 %0, [%1];" : "=r"(epoch) : "l"(&g_epoch) : "memory");
#pragma unroll
        for (int i = 0; i < 9; i++) {
            gx[i] = ldg32(reinterpret_cast<const uint32_t*>(gate_w) + i * 32 + lane);
            gx[9 + i] = ldg32(x32 + i * 32 + lane);
            gx[18 + i] = ldg32(x32 + 288 + i * 32 + lane);
        }
    }
    __syncthreads();
    if (CL) asm volatile("barrier.cluster.arrive.relaxed.aligned;" ::: "memory");

    if (warp == 8) {
        if (lane == 0) {
            wait_full(sm, 0);
            TS(12);
            for (int i = INFL0; i < NITEM; i++) {
                if (i >= INFL) wait_full(sm, i - INFL);
                if (i >= NST) mbar_wait(s2u(&sm.empty[i % NST]), (i / NST - 1) & 1);
                issue(i);
            }
            TS(1);
        }
        return;
    }

    const uint32_t tag = (epoch + 1u) & 3u;
    const int rowl = ((lane >> 4) << 3) + (lane & 7);
    const int chl = (lane >> 3) & 1;
    const float SC = 0.08838834764831845f * 1.4426950408889634f;
    const int rank = c & 7;
    float g0, g1;

    if (warp >= 4) {
        const int w = warp - 4, t = tid - 128;
        const int r4 = lane >> 2;
        if (t == 0) TS(14);
        {
            float acc[2][4] = {};
#pragma unroll
            for (int j = 0; j < 3; j++) {
                wait_full(sm, j);
#pragma unroll
                for (int i = 0; i < 3; i++) {
                    const int r = (w * 3 + i) * 16 + rowl;
#pragma unroll
                    for (int mt = 0; mt < 2; mt++) {
                        uint32_t a[4];
                        ldsm4t(a, ring + j * SLOT + r * 64 + (((mt * 2 + chl) ^ ((r >> 1) & 3)) << 4));
                        mma(acc[mt], a[0], a[1], a[2], a[3], xf[(j * 3 + i) * 2], xf[(j * 3 + i) * 2 + 1]);
                    }
                }
                __syncwarp();
                if (lane == 0) release(sm, j);
            }
            if ((lane & 3) == 0) {
#pragma unroll
                for (int mt = 0; mt < 2; mt++) {
                    sm.red[w][0][mt * 16 + r4] = acc[mt][0];
                    sm.red[w][1][mt * 16 + r4] = acc[mt][1];
                    sm.red[w][0][mt * 16 + r4 + 8] = acc[mt][2];
                    sm.red[w][1][mt * 16 + r4 + 8] = acc[mt][3];
                }
            }
            bar_sync(1, 128);
            const int bq = t >> 6, p = t & 15;
            float q0 = 0.f, q1 = 0.f;
#pragma unroll
            for (int k = 0; k < 4; k++) { const float2 v = *reinterpret_cast<const float2*>(&sm.red[k][bq][p * 2]); q0 += v.x; q1 += v.y; }
            if (CL) {
                asm volatile("barrier.cluster.wait.acquire.aligned;" ::: "memory");
                const uint32_t dst = t >> 4;
                st_async1(mapa(s2u(&sm.qs[0][0] + rank * 16 + p), dst), pack_bf16(q0, q1), mapa(s2u(&sm.qbar), dst));
            } else if (((t >> 4) & 3) == 0) {
                st_msg2(&g_q[bq * 4096 + c * 32 + p * 2], q0, q1, tag);
            }
            if (t == 0) TS(2);
            bar_sync(1, 128);
        }
        gate(gx, g0, g1);
        {
            float acc[3][4] = {};
#pragma unroll
            for (int j = 0; j < 3; j++) {
                wait_full(sm, I_W1 + j);
#pragma unroll
                for (int i = 0; i < 3; i++) {
                    const uint32_t base = ring + ((I_W1 + j) % NST) * SLOT + ((w * 3 + i) * 16 + rowl) * 80 + chl * 16;
#pragma unroll
                    for (int mt = 0; mt < 3; mt++) {
                        uint32_t a[4];
                        ldsm4t(a, base + mt * 32);
                        mma(acc[mt], a[0], a[1], a[2], a[3], xf[(j * 3 + i) * 2], xf[(j * 3 + i) * 2 + 1]);
                    }
                }
            }
            if ((lane & 3) == 0) {
#pragma unroll
                for (int mt = 0; mt < 3; mt++) {
                    sm.red[w][0][mt * 16 + r4] = acc[mt][0];
                    sm.red[w][1][mt * 16 + r4] = acc[mt][1];
                    sm.red[w][0][mt * 16 + r4 + 8] = acc[mt][2];
                    sm.red[w][1][mt * 16 + r4 + 8] = acc[mt][3];
                }
            }
            bar_sync(1, 128);
            if (t < 96) {
                const int bb = t >= 48, k = t - bb * 48;
                float h = 0.f;
                if (k < 36) {
                    const int kk = k + (c & 1) * 4;
                    h = bf_round(sm.red[0][bb][kk] + sm.red[1][bb][kk] + sm.red[2][bb][kk] + sm.red[3][bb][kk]);
                    h = fmaxf(bf_round(h + bf_lo(bias_raw)), 0.f);
                }
                reinterpret_cast<__nv_bfloat16*>(sm.hs)[t] = __float2bfloat16_rn(h * h);
            }
            bar_sync(1, 128);
        }
        float acc[9][4] = {};
        {
            uint32_t hb[6];
#pragma unroll
            for (int ks = 0; ks < 3; ks++) { hb[2 * ks] = sm.hs[r4 & 1][ks * 8 + (lane & 3)]; hb[2 * ks + 1] = sm.hs[r4 & 1][ks * 8 + 4 + (lane & 3)]; }
#pragma unroll
            for (int j = 0; j < 3; j++) {
                wait_full(sm, I_W2 + j);
#pragma unroll
                for (int i = 0; i < 3; i++) {
                    const int mt = w * 3 + i;
#pragma unroll
                    for (int ks = 0; ks < 3; ks++) {
                        const int r = (mt >> 2) * 36 + min(ks * 16 + rowl, 35);
                        uint32_t a[4];
                        ldsm4t(a, ring + ((I_W2 + j) % NST) * SLOT + r * 128 + ((((mt & 3) * 2 + chl) ^ (r & 7)) << 4));
                        mma(acc[j * 3 + i], a[0], a[1], a[2], a[3], hb[2 * ks], hb[2 * ks + 1]);
                    }
                }
            }
#pragma unroll
            for (int j = 0; j < 9; j++) { acc[j][0] *= 1.f - g0; acc[j][1] *= 1.f - g1; acc[j][2] *= 1.f - g0; acc[j][3] *= 1.f - g1; }
        }
        if (t == 0) TS(3);
        {
            mbar_wait_cluster(s2u(&sm.obar));
            if (t == 0) TS(9);
            const int bb = r4 & 1;
            float f[4];
            {
                float2 ml[4];
#pragma unroll
                for (int s = 0; s < 4; s++) ml[s] = *reinterpret_cast<const float2*>(&sm.obuf[bb * 4 + s][32]);
                const float M = fmaxf(fmaxf(ml[0].x, ml[1].x), fmaxf(ml[2].x, ml[3].x));
                float L = 0.f;
#pragma unroll
                for (int s = 0; s < 4; s++) { f[s] = ex2((ml[s].x - M) * SC); L = fmaf(f[s], ml[s].y, L); }
                const float inv = (bb ? g1 : g0) * rcp(L);
#pragma unroll
                for (int s = 0; s < 4; s++) f[s] *= inv;
            }
            uint32_t ob[4];
#pragma unroll
            for (int k = 0; k < 4; k++) {
                float o0 = 0.f, o1 = 0.f;
#pragma unroll
                for (int s = 0; s < 4; s++) {
                    const float2 v = *reinterpret_cast<const float2*>(&sm.obuf[bb * 4 + s][k * 8 + (lane & 3) * 2]);
                    o0 = fmaf(f[s], v.x, o0);
                    o1 = fmaf(f[s], v.y, o1);
                }
                ob[k] = pack_bf16(o0, o1);
            }
#pragma unroll
            for (int j = 0; j < 3; j++) {
                wait_full(sm, I_WO + j);
#pragma unroll
                for (int i = 0; i < 3; i++) {
                    const int mt = w * 3 + i;
#pragma unroll
                    for (int ks = 0; ks < 2; ks++) {
                        const int r = (mt >> 2) * 32 + ks * 16 + rowl;
                        uint32_t a[4];
                        ldsm4t(a, ring + ((I_WO + j) % NST) * SLOT + r * 128 + ((((mt & 3) * 2 + chl) ^ (r & 7)) << 4));
                        mma(acc[j * 3 + i], a[0], a[1], a[2], a[3], ob[2 * ks], ob[2 * ks + 1]);
                    }
                }
            }
            if (t == 0) TS(4);
        }
        {
            const int j = lane & 3;
            float* dst = g_fin + ((size_t)(w * 6 + (j & 1)) * NCTA + c) * 16 + r4 * 2;
#pragma unroll
            for (int it = 0; it < 5; it++) {
                const int t0 = 2 * it, t1 = (2 * it + 1 < 9) ? 2 * it + 1 : 2 * it;
                const float u0 = (j & 2) ? acc[t1][0] : acc[t0][0], u1 = (j & 2) ? acc[t1][1] : acc[t0][1];
                const float u2 = (j & 2) ? acc[t1][2] : acc[t0][2], u3 = (j & 2) ? acc[t1][3] : acc[t0][3];
                const int own = (j & 2) ? (t1 / 3) * 24 + (t1 % 3) * 2 : (t0 / 3) * 24 + (t0 % 3) * 2;
                if (it < 4 || j < 2) st_msg2(dst + (size_t)own * NCTA * 16, (j & 1) ? u2 : u0, (j & 1) ? u3 : u1, tag);
            }
        }
        if (t == 0) TS(5);
        return;
    }

    gate(gx, g0, g1);
    if (CL) {
        mbar_wait_cluster(s2u(&sm.qbar));
    } else {
        const float* qp = g_q + ((c >> 2) & 1) * 4096 + (c >> 3) * 256 + tid * 2;
        uint2 v;
        int it = 0;
        do { v = ld_msg2(qp); } while (!ok2(v, tag) && ++it < SPIN_LIMIT);
        (&sm.qs[0][0])[tid] = pack_bf16(__uint_as_float(v.x), __uint_as_float(v.y));
        bar_sync(3, 128);
    }
    if (tid == 0) TS(6);
    uint32_t qf[16];
#pragma unroll
    for (int ks = 0; ks < 8; ks++) {
        qf[2 * ks] = lane < 8 ? sm.qs[lane >> 2][ks * 8 + (lane & 3)] : 0u;
        qf[2 * ks + 1] = lane < 8 ? sm.qs[lane >> 2][ks * 8 + 4 + (lane & 3)] : 0u;
    }
    float o[8][4] = {};
    float m = -INFINITY, l = 0.f;
    const int key = warp * 16 + rowl;
    const uint32_t off = key * 128;
    const int sw = key & 7;
#pragma unroll 1
    for (int tl = 0; tl < 16; tl++) {
        const int ik = I_KV + 2 * tl, iv = ik + 1;
        wait_full(sm, ik);
        const uint32_t kb = ring + (ik % NST) * SLOT + off;
        float s[2][2][4] = {};
#pragma unroll
        for (int ks = 0; ks < 8; ks++) {
            uint32_t kf[4];
            ldsm4(kf, kb + (ks >> 2) * 8192 + ((((ks & 3) * 2 + chl) ^ sw) << 4));
            mma(s[0][ks & 1], qf[2 * ks], 0u, qf[2 * ks + 1], 0u, kf[0], kf[1]);
            mma(s[1][ks & 1], qf[2 * ks], 0u, qf[2 * ks + 1], 0u, kf[2], kf[3]);
        }
        __syncwarp();
        if (lane == 0) release(sm, ik);
        const float s0 = s[0][0][0] + s[0][1][0], s1 = s[0][0][1] + s[0][1][1];
        const float s2 = s[1][0][0] + s[1][1][0], s3 = s[1][0][1] + s[1][1][1];
        float mx = fmaxf(fmaxf(s0, s1), fmaxf(s2, s3));
        mx = fmaxf(mx, __shfl_xor_sync(~0u, mx, 1));
        mx = fmaxf(mx, __shfl_xor_sync(~0u, mx, 2));
        const float mn = fmaxf(m, mx);
        const float al = ex2((m - mn) * SC);
        m = mn;
        const float ms = mn * SC;
        const uint32_t p0 = pack_bf16(ex2(fmaf(s0, SC, -ms)), ex2(fmaf(s1, SC, -ms)));
        const uint32_t p1 = pack_bf16(ex2(fmaf(s2, SC, -ms)), ex2(fmaf(s3, SC, -ms)));
        l = fmaf(l, al, (bf_lo(p0) + bf_hi(p0)) + (bf_lo(p1) + bf_hi(p1)));
        const float a0 = __shfl_sync(~0u, al, 0), a1 = __shfl_sync(~0u, al, 4);
        if (a0 != 1.f || a1 != 1.f) {
#pragma unroll
            for (int mt = 0; mt < 8; mt++) { o[mt][0] *= a0; o[mt][1] *= a1; o[mt][2] *= a0; o[mt][3] *= a1; }
        }
        wait_full(sm, iv);
        const uint32_t vb = ring + (iv % NST) * SLOT + off;
#pragma unroll
        for (int mt = 0; mt < 8; mt++) {
            uint32_t vf[4];
            ldsm4t(vf, vb + (mt >> 2) * 8192 + ((((mt & 3) * 2 + chl) ^ sw) << 4));
            mma(o[mt], vf[0], vf[1], vf[2], vf[3], p0, p1);
        }
        __syncwarp();
        if (lane == 0) release(sm, iv);
    }
    if (tid == 0) TS(7);
    l += __shfl_xor_sync(~0u, l, 1);
    l += __shfl_xor_sync(~0u, l, 2);
    if (lane == 0 || lane == 4) { sm.ml[warp][lane >> 2][0] = m; sm.ml[warp][lane >> 2][1] = l; }
    if ((lane & 3) == 0) {
        const int r = lane >> 2;
#pragma unroll
        for (int mt = 0; mt < 8; mt++) {
            sm.ocomb[warp][0][mt * 16 + r] = o[mt][0];
            sm.ocomb[warp][1][mt * 16 + r] = o[mt][1];
            sm.ocomb[warp][0][mt * 16 + r + 8] = o[mt][2];
            sm.ocomb[warp][1][mt * 16 + r + 8] = o[mt][3];
        }
    }
    bar_sync(3, 128);
    {
        const int h = tid >> 6, d = (tid & 63) * 2;
        const float M = fmaxf(fmaxf(sm.ml[0][h][0], sm.ml[1][h][0]), fmaxf(sm.ml[2][h][0], sm.ml[3][h][0]));
        float L = 0.f, O0 = 0.f, O1 = 0.f;
#pragma unroll
        for (int w = 0; w < 4; w++) {
            const float sc = ex2((sm.ml[w][h][0] - M) * SC);
            const float2 ov = *reinterpret_cast<const float2*>(&sm.ocomb[w][h][d]);
            L = fmaf(sc, sm.ml[w][h][1], L);
            O0 = fmaf(sc, ov.x, O0);
            O1 = fmaf(sc, ov.y, O1);
        }
        const int dr = tid >> 4;
        if (CL) {
            asm volatile("barrier.cluster.wait.acquire.aligned;" ::: "memory");
            const uint32_t dst = mapa(s2u(&sm.obuf[rank][0]), dr), bar = mapa(s2u(&sm.obar), dr);
            st_async2(dst + (d & 31) * 4, O0, O1, bar);
            if ((d & 31) == 0) st_async2(dst + 128, M, L, bar);
        } else {
            float* dst = g_o + ((size_t)((c & ~7) + dr) * 8 + rank) * 40;
            st_msg2(dst + (d & 31), O0, O1, tag);
            if ((d & 31) < 8) st_msg2(dst + 32 + (d & 31), M, L, tag);
            const float* src = g_o + ((size_t)c * 8 + dr) * 40;
            uint2 v, ml;
            int it = 0;
            do { v = ld_msg2(src + (d & 31)); ml = ld_msg2(src + 32); } while (!(ok2(v, tag) && ok2(ml, tag)) && ++it < SPIN_LIMIT);
            *reinterpret_cast<uint2*>(&sm.obuf[dr][d & 31]) = v;
            if ((d & 31) == 0) *reinterpret_cast<uint2*>(&sm.obuf[dr][32]) = ml;
            mbar_arrive(s2u(&sm.obar));
        }
    }
    if (tid == 0) TS(8);

    if (c < NRED) {
        const float bias_out = ((tid & 1) ? 1.f - g1 : 1.f - g0) * bf_lo(bias_raw);
        const float* src = g_fin + (size_t)c * NCTA * 16 + tid * 4;
        __nv_bfloat16* dst = out + (tid & 1) * D_MODEL + c * 8 + ((tid & 15) >> 1);
        uint4 v[4];
#pragma unroll
        for (int i = 0; i < 4; i++) v[i] = make_uint4(tag ^ 1u, 0u, 0u, 0u);
        int it = 0;
        bool all;
        do {
#pragma unroll
            for (int i = 0; i < 4; i++) ld_msg4_if(v[i], src + i * 512, !ok4(v[i], tag));
            const bool ok = ok4(v[0], tag) && ok4(v[1], tag) && ok4(v[2], tag) && ok4(v[3], tag);
            float r0 = (__uint_as_float(v[0].x) + __uint_as_float(v[1].x)) + (__uint_as_float(v[2].x) + __uint_as_float(v[3].x));
            float r1 = (__uint_as_float(v[0].y) + __uint_as_float(v[1].y)) + (__uint_as_float(v[2].y) + __uint_as_float(v[3].y));
            const float r2 = (__uint_as_float(v[0].z) + __uint_as_float(v[1].z)) + (__uint_as_float(v[2].z) + __uint_as_float(v[3].z));
            const float r3 = (__uint_as_float(v[0].w) + __uint_as_float(v[1].w)) + (__uint_as_float(v[2].w) + __uint_as_float(v[3].w));
            const bool hi = lane & 16;
            const float t0 = __shfl_xor_sync(~0u, hi ? r0 : r2, 16), t1 = __shfl_xor_sync(~0u, hi ? r1 : r3, 16);
            r0 = (hi ? r2 : r0) + t0;
            r1 = (hi ? r3 : r1) + t1;
            const bool hi2 = lane & 8;
            const float t2 = __shfl_xor_sync(~0u, hi2 ? r0 : r1, 8);
            r0 = (hi2 ? r1 : r0) + t2;
            r0 += __shfl_xor_sync(~0u, r0, 4);
            float* fin = &sm.fin[it & 1][0][0];
            if (!(lane & 4)) fin[warp * 16 + (lane & 3) * 4 + (lane >> 4) * 2 + ((lane >> 3) & 1)] = r0;
            all = bar_and(3, 128, ok);
            const float r = bias_out + ((fin[tid & 15] + fin[16 + (tid & 15)]) + (fin[32 + (tid & 15)] + fin[48 + (tid & 15)]));
            asm volatile("{\n.reg .pred p;\nsetp.ne.u32 p, %2, 0;\n@p st.global.u16 [%0], %1;\n}" ::"l"(dst),
                         "h"(__bfloat16_as_ushort(__float2bfloat16_rn(r))), "r"((uint32_t)(all && tid < 16)) : "memory");
        } while (!all && ++it < SPIN_LIMIT);
        if (c == 0 && tid == 0) g_epoch = epoch + 1u;
        if (tid == 0) TS(10);
    }
}

typedef CUresult (*EncFn)(CUtensorMap*, CUtensorMapDataType, cuuint32_t, void*, const cuuint64_t*, const cuuint64_t*,
                          const cuuint32_t*, const cuuint32_t*, CUtensorMapInterleave, CUtensorMapSwizzle,
                          CUtensorMapL2promotion, CUtensorMapFloatOOBfill);

}

extern "C" void kernel_launch(void* const* d_in, const int* in_sizes, int n_in, void* d_out, int out_size) {
    (void)in_sizes; (void)n_in; (void)out_size;
    EncFn enc = nullptr;
    cudaDriverEntryPointQueryResult qr;
    cudaGetDriverEntryPoint("cuTensorMapEncodeTiled", (void**)&enc, cudaEnableDefault, &qr);
    CUtensorMap mK, mV, mWq, mW1, mW2, mWo;
    const CUtensorMapL2promotion pr = CU_TENSOR_MAP_L2_PROMOTION_L2_256B;
    auto mk3 = [&](CUtensorMap* m, void* p, uint64_t rows, uint64_t rowbytes, uint32_t nblk, uint32_t brows, uint32_t bblk) {
        cuuint64_t d[3] = {64, rows, nblk}, s[2] = {rowbytes, 128};
        cuuint32_t b[3] = {64, brows, bblk}, e[3] = {1, 1, 1};
        enc(m, CU_TENSOR_MAP_DATA_TYPE_BFLOAT16, 3, p, d, s, b, e, CU_TENSOR_MAP_INTERLEAVE_NONE, CU_TENSOR_MAP_SWIZZLE_128B, pr,
            CU_TENSOR_MAP_FLOAT_OOB_FILL_NONE);
    };
    auto mk2 = [&](CUtensorMap* m, void* p, uint64_t cols, uint32_t bcols, CUtensorMapSwizzle sw) {
        cuuint64_t d[2] = {cols, 576}, s[1] = {cols * 2};
        cuuint32_t b[2] = {bcols, 192}, e[2] = {1, 1};
        enc(m, CU_TENSOR_MAP_DATA_TYPE_BFLOAT16, 2, p, d, s, b, e, CU_TENSOR_MAP_INTERLEAVE_NONE, sw, pr,
            CU_TENSOR_MAP_FLOAT_OOB_FILL_NONE);
    };
    mk3(&mK, d_in[1], 32ull * SK, 256, 2, 64, 2);
    mk3(&mV, d_in[2], 32ull * SK, 256, 2, 64, 2);
    mk2(&mWq, d_in[3], 4096, 32, CU_TENSOR_MAP_SWIZZLE_64B);
    mk2(&mW1, d_in[6], 4608, 40, CU_TENSOR_MAP_SWIZZLE_NONE);
    mk3(&mW2, d_in[8], 4608, 1152, 9, 36, 3);
    mk3(&mWo, d_in[4], 4096, 1152, 9, 32, 3);
    const int smem = NST * SLOT + 1024;
    cudaFuncSetAttribute(fused_kernel<true>, cudaFuncAttributeMaxDynamicSharedMemorySize, smem);
    cudaFuncSetAttribute(fused_kernel<false>, cudaFuncAttributeMaxDynamicSharedMemorySize, smem);

    cudaLaunchConfig_t cfg = {};
    cfg.gridDim = dim3(NCTA);
    cfg.blockDim = dim3(288);
    cfg.dynamicSmemBytes = smem;
    cfg.stream = cudaStreamPerThread;
    cudaLaunchAttribute at[1];
    at[0].id = cudaLaunchAttributeClusterDimension;
    at[0].val.clusterDim.x = 8; at[0].val.clusterDim.y = 1; at[0].val.clusterDim.z = 1;
    cfg.attrs = at;
    cfg.numAttrs = 1;
    int ncl = 0;
    if (cudaOccupancyMaxActiveClusters(&ncl, fused_kernel<true>, &cfg) != cudaSuccess) { ncl = 0; cudaGetLastError(); }
    const __nv_bfloat16 *x = (const __nv_bfloat16*)d_in[0], *b1 = (const __nv_bfloat16*)d_in[7], *b2 = (const __nv_bfloat16*)d_in[9],
                        *gw = (const __nv_bfloat16*)d_in[10];
    if (ncl >= NCTA / 8) {
        cudaLaunchKernelEx(&cfg, fused_kernel<true>, mK, mV, mWq, mW1, mW2, mWo, x, b1, b2, gw, (__nv_bfloat16*)d_out);
    } else {
        cfg.numAttrs = 0;
        cudaLaunchKernelEx(&cfg, fused_kernel<false>, mK, mV, mWq, mW1, mW2, mWo, x, b1, b2, gw, (__nv_bfloat16*)d_out);
    }
}
```

```cpp
#include <cuda_runtime.h>
#include <cuda_bf16.h>
#include <cuda.h>
#include <stdint.h>

namespace {

constexpr int D_MODEL = 576;
constexpr int SK = 32768;
constexpr int WIN = 4096;
constexpr int NCTA = 128;
constexpr int NRED = 144;
constexpr int SLOT = 16384;
#define NST 12
#define INFL 4
constexpr int I_KV = 3, I_W1 = 35, I_W2 = 38, I_WO = 41, NITEM = 44;
#define NP 1
#define I_POLL 41
constexpr int SPIN_LIMIT = 1 << 17;

struct Scratch {
    float fin[NRED * NCTA * 8];
    float o[NCTA * 8 * 40];
    float q[2 * 4096];
    unsigned epoch, pad[3];
};
__device__ __align__(128) Scratch g_scr;
#define TS(i) do {} while (0)

struct __align__(16) Smem {
    uint64_t full[NST + 9];
    uint64_t empty[NST + ((NST * 2 + 9) & 1)];
    uint64_t obar, xbar;
    uint32_t xs[2 * 288];
    uint32_t gw[288];
    uint32_t ep[4];
    float red[4][2][48];
    float ocomb[4][2][128];
    float ml[4][2][2];
    float obuf[8][40];
    uint32_t qs[2][64];
    uint32_t hs[2][24];
};

__device__ __forceinline__ uint32_t s2u(const void* p) { return (uint32_t)__cvta_generic_to_shared(p); }
__device__ __forceinline__ void mbar_init(uint32_t a, int c) { asm volatile("mbarrier.init.shared.b64 [%0], %1;" ::"r"(a), "r"(c) : "memory"); }
__device__ __forceinline__ void mbar_expect(uint32_t a, uint32_t b) { asm volatile("mbarrier.arrive.expect_tx.shared.b64 _, [%0], %1;" ::"r"(a), "r"(b) : "memory"); }
__device__ __forceinline__ void mbar_arrive(uint32_t a) { asm volatile("mbarrier.arrive.shared.b64 _, [%0];" ::"r"(a) : "memory"); }
__device__ __forceinline__ void mbar_wait(uint32_t a, uint32_t ph) {
    uint32_t ok;
    int it = 0;
    do {
        asm volatile("{\n.reg .pred p;\nmbarrier.try_wait.parity.shared.b64 p, [%1], %2;\nselp.u32 %0, 1, 0, p;\n}" : "=r"(ok) : "r"(a), "r"(ph) : "memory");
    } while (!ok && ++it < SPIN_LIMIT);
}
__device__ __forceinline__ void tma2d(uint32_t dst, const CUtensorMap* m, int c0, int c1, uint32_t bar) {
    asm volatile("cp.async.bulk.tensor.2d.shared::cluster.global.mbarrier::complete_tx::bytes [%0], [%1, {%3, %4}], [%2];" ::"r"(dst), "l"(m), "r"(bar), "r"(c0), "r"(c1) : "memory");
}
__device__ __forceinline__ void tma3d_ef(uint32_t dst, const CUtensorMap* m, int c0, int c1, int c2, uint32_t bar, uint64_t pol) {
    asm volatile("cp.async.bulk.tensor.3d.shared::cluster.global.mbarrier::complete_tx::bytes.L2::cache_hint [%0], [%1, {%3, %4, %5}], [%2], %6;"
                 ::"r"(dst), "l"(m), "r"(bar), "r"(c0), "r"(c1), "r"(c2), "l"(pol) : "memory");
}
__device__ __forceinline__ void bulk(uint32_t dst, const void* src, uint32_t bytes, uint32_t bar) {
    asm volatile("cp.async.bulk.shared::cluster.global.mbarrier::complete_tx::bytes [%0], [%1], %2, [%3];" ::"r"(dst), "l"(src), "r"(bytes), "r"(bar) : "memory");
}
__device__ __forceinline__ void ldsm4(uint32_t* r, uint32_t a) {
    asm volatile("ldmatrix.sync.aligned.m8n8.x4.shared.b16 {%0,%1,%2,%3}, [%4];" : "=r"(r[0]), "=r"(r[1]), "=r"(r[2]), "=r"(r[3]) : "r"(a) : "memory");
}
__device__ __forceinline__ void ldsm4t(uint32_t* r, uint32_t a) {
    asm volatile("ldmatrix.sync.aligned.m8n8.x4.trans.shared.b16 {%0,%1,%2,%3}, [%4];" : "=r"(r[0]), "=r"(r[1]), "=r"(r[2]), "=r"(r[3]) : "r"(a) : "memory");
}
__device__ __forceinline__ void mma(float* c, uint32_t a0, uint32_t a1, uint32_t a2, uint32_t a3, uint32_t b0, uint32_t b1) {
    asm volatile("mma.sync.aligned.m16n8k16.row.col.f32.bf16.bf16.f32 {%0,%1,%2,%3}, {%4,%5,%6,%7}, {%8,%9}, {%0,%1,%2,%3};"
                 : "+f"(c[0]), "+f"(c[1]), "+f"(c[2]), "+f"(c[3]) : "r"(a0), "r"(a1), "r"(a2), "r"(a3), "r"(b0), "r"(b1));
}
__device__ __forceinline__ uint32_t pack_bf16(float lo, float hi) {
    uint32_t r;
    asm("cvt.rn.bf16x2.f32 %0, %1, %2;" : "=r"(r) : "f"(hi), "f"(lo));
    return r;
}
__device__ __forceinline__ float bf_lo(uint32_t v) { return __uint_as_float(v << 16); }
__device__ __forceinline__ float bf_hi(uint32_t v) { return __uint_as_float(v & 0xffff0000u); }
__device__ __forceinline__ float bf_round(float v) { return __bfloat162float(__float2bfloat16_rn(v)); }
__device__ __forceinline__ float ex2(float v) { float r; asm("ex2.approx.ftz.f32 %0, %1;" : "=f"(r) : "f"(v)); return r; }
__device__ __forceinline__ float rcp(float v) { float r; asm("rcp.approx.ftz.f32 %0, %1;" : "=f"(r) : "f"(v)); return r; }
__device__ __forceinline__ uint32_t ldg32(const void* p) {
    uint32_t v;
    asm volatile("ld.global.nc.u32 %0, [%1];" : "=r"(v) : "l"(p));
    return v;
}
__device__ __forceinline__ uint32_t ldg16(const void* p) {
    uint32_t v;
    asm volatile("ld.global.nc.u16 %0, [%1];" : "=r"(v) : "l"(p));
    return v;
}
__device__ __forceinline__ uint32_t tagw(float v, uint32_t tag) { return (__float_as_uint(v) & ~3u) | tag; }
__device__ __forceinline__ void st_msg2(float* p, float a, float b, uint32_t tag) {
    asm volatile("st.volatile.global.v2.u32 [%0], {%1,%2};" ::"l"(p), "r"(tagw(a, tag)), "r"(tagw(b, tag)) : "memory");
}
__device__ __forceinline__ uint2 ld_msg2(const float* p) {
    uint2 v;
    asm volatile("ld.volatile.global.v2.u32 {%0,%1}, [%2];" : "=r"(v.x), "=r"(v.y) : "l"(p) : "memory");
    return v;
}
__device__ __forceinline__ void ld_msg2_if(uint2& v, const float* p, bool pred) {
    asm volatile("{\n.reg .pred p;\nsetp.ne.u32 p, %3, 0;\n@p ld.volatile.global.v2.u32 {%0,%1}, [%2];\n}"
                 : "+r"(v.x), "+r"(v.y) : "l"(p), "r"((uint32_t)pred) : "memory");
}
__device__ __forceinline__ void ld_msg4_if(uint4& v, const float* p, uint32_t pred) {
    asm volatile("{\n.reg .pred p;\nsetp.ne.u32 p, %5, 0;\n@p ld.volatile.global.v4.u32 {%0,%1,%2,%3}, [%4];\n}"
                 : "+r"(v.x), "+r"(v.y), "+r"(v.z), "+r"(v.w) : "l"(p), "r"((uint32_t)pred) : "memory");
}
__device__ __forceinline__ uint4 ld_msg4(const float* p) {
    uint4 v;
    asm volatile("ld.volatile.global.v4.u32 {%0,%1,%2,%3}, [%4];" : "=r"(v.x), "=r"(v.y), "=r"(v.z), "=r"(v.w) : "l"(p) : "memory");
    return v;
}
__device__ __forceinline__ bool ok2(uint2 v, uint32_t tag) { return (((v.x ^ tag) | (v.y ^ tag)) & 3u) == 0; }
__device__ __forceinline__ bool ok4(uint4 v, uint32_t tag) { return (((v.x ^ tag) | (v.y ^ tag) | (v.z ^ tag) | (v.w ^ tag)) & 3u) == 0; }
__device__ __forceinline__ void bar_sync(int id, int n) { asm volatile("bar.sync %0, %1;" ::"r"(id), "r"(n) : "memory"); }
__device__ __forceinline__ uint32_t full_bar(Smem& sm, int i) { return s2u(&sm.full[i < I_W1 ? i % NST : NST + i - I_W1]); }
__device__ __forceinline__ void wait_full(Smem& sm, int i) { mbar_wait(full_bar(sm, i), i < I_W1 ? (i / NST) & 1 : 0); }
__device__ __forceinline__ void release(Smem& sm, int i) { mbar_arrive(s2u(&sm.empty[i % NST])); }

__device__ __forceinline__ void gate(const Smem& sm, int lane, float& g0, float& g1) {
    float s0 = 0.f, s1 = 0.f;
#pragma unroll
    for (int i = 0; i < 9; i++) {
        const uint32_t gv = sm.gw[i * 32 + lane], a = sm.xs[i * 32 + lane], b = sm.xs[288 + i * 32 + lane];
        s0 = fmaf(bf_lo(gv), bf_lo(a), fmaf(bf_hi(gv), bf_hi(a), s0));
        s1 = fmaf(bf_lo(gv), bf_lo(b), fmaf(bf_hi(gv), bf_hi(b), s1));
    }
#pragma unroll
    for (int o = 16; o; o >>= 1) { s0 += __shfl_xor_sync(~0u, s0, o); s1 += __shfl_xor_sync(~0u, s1, o); }
    g0 = 1.f / (1.f + __expf(-s0));
    g1 = 1.f / (1.f + __expf(-s1));
}

__global__ void __launch_bounds__(288, 1)
fused_kernel(const __grid_constant__ CUtensorMap mWq, const __grid_constant__ CUtensorMap mK,
             const __grid_constant__ CUtensorMap mV, const __grid_constant__ CUtensorMap mW1,
             const __grid_constant__ CUtensorMap mW2, const __grid_constant__ CUtensorMap mWo,
             const __nv_bfloat16* __restrict__ x, const __nv_bfloat16* __restrict__ b1,
             const __nv_bfloat16* __restrict__ b2, const __nv_bfloat16* __restrict__ gate_w,
             __nv_bfloat16* __restrict__ out, Scratch* __restrict__ scr) {
    extern __shared__ __align__(1024) unsigned char smem_raw[];
    __shared__ Smem sm;
    const uint32_t ring = (s2u(smem_raw) + 1023u) & ~1023u;
    const int tid = threadIdx.x, lane = tid & 31;
    const int c = blockIdx.x;

    const int kvrow = ((((c >> 2) & 1) * 16 + (c >> 3)) * SK) + (SK - WIN) + (c & 3) * 1024;
    uint64_t pol;
    asm volatile("createpolicy.fractional.L2::evict_first.b64 %0, 1.0;" : "=l"(pol));
    auto issue = [&](int i) {
        const uint32_t dst = ring + (i % NST) * SLOT, bar = full_bar(sm, i);
        if (i < I_KV) {
            mbar_expect(bar, 192 * 64);
            tma2d(dst, &mWq, c * 32, i * 192, bar);
        } else if (i < I_W1) {
            mbar_expect(bar, 16384);
            tma3d_ef(dst, ((i - I_KV) & 1) ? &mV : &mK, 0, kvrow + ((i - I_KV) >> 1) * 64, 0, bar, pol);
        } else if (i < I_W2) {
            mbar_expect(bar, 192 * 80);
            tma2d(dst, &mW1, (c * 36) & ~7, (i - I_W1) * 192, bar);
        } else if (i < I_WO) {
            mbar_expect(bar, 36 * 384);
            tma3d_ef(dst, &mW2, 0, c * 36, (i - I_W2) * 3, bar, pol);
        } else {
            mbar_expect(bar, 32 * 384);
            tma3d_ef(dst, &mWo, 0, c * 32, (i - I_WO) * 3, bar, pol);
        }
    };
    if (tid == 0) {
        TS(0);
#pragma unroll
        for (int i = 0; i < INFL; i++) mbar_init(s2u(&sm.full[i]), 1);
        asm volatile("fence.proxy.async.shared::cta;" ::: "memory");
#pragma unroll
        for (int i = 0; i < INFL; i++) issue(i);
        TS(11);
#pragma unroll
        for (int i = INFL; i < NST + 9; i++) mbar_init(s2u(&sm.full[i]), 1);
#pragma unroll
        for (int i = 0; i < NST; i++) mbar_init(s2u(&sm.empty[i]), 4);
        mbar_init(s2u(&sm.obar), 128);
        asm volatile("fence.proxy.async.shared::cta;" ::: "memory");
    }
    const int warp = __shfl_sync(~0u, tid >> 5, 0);
    if (warp == 0) {
        asm volatile("bar.arrive 0, 288;" ::: "memory");
        if (lane == 0) {
            asm volatile("prefetch.tensormap [%0];" ::"l"(&mW1) : "memory");
            asm volatile("prefetch.tensormap [%0];" ::"l"(&mW2) : "memory");
            asm volatile("prefetch.tensormap [%0];" ::"l"(&mWo) : "memory");
            TS(13);
#pragma unroll 1
            for (int i = INFL; i < NITEM; i++) {
                wait_full(sm, i - INFL);
                if (i >= NST) mbar_wait(s2u(&sm.empty[i % NST]), (i / NST - 1) & 1);
                issue(i);
            }
            TS(1);
        }
        return;
    }

    uint32_t xf[18], bias_raw = 0;
    const int t = (tid - 32) & 127, w = (warp - 1) & 3;
    const int rid = w * NCTA + c;
    if (tid == 32) {
        const uint32_t bar = s2u(&sm.xbar);
        mbar_init(bar, 1);
        asm volatile("fence.proxy.async.shared::cta;" ::: "memory");
        mbar_expect(bar, 2304 + 1152 + 16);
        bulk(s2u(sm.xs), x, 2304, bar);
        bulk(s2u(sm.ep), &scr->epoch, 16, bar);
        bulk(s2u(sm.gw), gate_w, 1152, bar);
    }
    if (warp > 4) {
        const int k = t % 48;
        if (k < 36) bias_raw = ldg16(b1 + c * 36 + k);
    } else if (rid < NRED) {
        bias_raw = ldg16(b2 + rid * 4 + (lane & 1) * 2 + ((lane >> 3) & 1));
    }
    bar_sync(0, 288);
    mbar_wait(s2u(&sm.xbar), 0);
    const uint32_t epoch = sm.ep[0];
    if (warp > 4) {
        const uint32_t* xp = sm.xs + ((lane >> 2) & 1) * 288 + w * 24 + (lane & 3);
#pragma unroll
        for (int j = 0; j < 9; j++) { xf[j * 2] = xp[j / 3 * 96 + j % 3 * 8]; xf[j * 2 + 1] = xp[j / 3 * 96 + j % 3 * 8 + 4]; }
    }

    const uint32_t tag = (epoch + 1u) & 3u;
    const int rowl = ((lane >> 4) << 3) + (lane & 7);
    const int chl = (lane >> 3) & 1;
    const float SC = 0.08838834764831845f * 1.4426950408889634f;
    const int rank = c & 7, r4 = lane >> 2;
    float g0, g1;
    int npass;
    asm volatile("mov.u32 %0, 2;" : "=r"(npass));

    if (warp > 4) {
        if (t == 0) TS(14);
        {
            float acc[2][4] = {};
#pragma unroll
            for (int j = 0; j < 3; j++) {
                wait_full(sm, j);
#pragma unroll
                for (int i = 0; i < 3; i++) {
                    const int r = (w * 3 + i) * 16 + rowl;
#pragma unroll
                    for (int mt = 0; mt < 2; mt++) {
                        uint32_t a[4];
                        ldsm4t(a, ring + j * SLOT + r * 64 + (((mt * 2 + chl) ^ ((r >> 1) & 3)) << 4));
                        mma(acc[mt], a[0], a[1], a[2], a[3], xf[(j * 3 + i) * 2], xf[(j * 3 + i) * 2 + 1]);
                    }
                }
                __syncwarp();
                if (lane == 0) release(sm, j);
            }
            if ((lane & 3) == 0) {
#pragma unroll
                for (int mt = 0; mt < 2; mt++) {
                    sm.red[w][0][mt * 16 + r4] = acc[mt][0];
                    sm.red[w][1][mt * 16 + r4] = acc[mt][1];
                    sm.red[w][0][mt * 16 + r4 + 8] = acc[mt][2];
                    sm.red[w][1][mt * 16 + r4 + 8] = acc[mt][3];
                }
            }
            bar_sync(1, 128);
            if (t < 32) {
                const int bq = t >> 4, p = t & 15;
                float q0 = 0.f, q1 = 0.f;
#pragma unroll
                for (int k = 0; k < 4; k++) { const float2 v = *reinterpret_cast<const float2*>(&sm.red[k][bq][p * 2]); q0 += v.x; q1 += v.y; }
                st_msg2(&scr->q[bq * 4096 + c * 32 + p * 2], q0, q1, tag);
            }
            if (t == 0) TS(2);
            bar_sync(1, 128);
        }
        gate(sm, lane, g0, g1);
#pragma unroll 1
        for (int pass = 0; pass < npass; pass++) {
            {
                float acc[3][4] = {};
#pragma unroll
                for (int j = 0; j < 3; j++) {
                    if (pass) wait_full(sm, I_W1 + j);
#pragma unroll
                    for (int i = 0; i < 3; i++) {
                        const uint32_t base = ring + ((I_W1 + j) % NST) * SLOT + ((w * 3 + i) * 16 + rowl) * 80 + chl * 16;
#pragma unroll
                        for (int mt = 0; mt < 3; mt++) {
                            uint32_t a[4];
                            ldsm4t(a, base + mt * 32);
                            mma(acc[mt], a[0], a[1], a[2], a[3], xf[(j * 3 + i) * 2], xf[(j * 3 + i) * 2 + 1]);
                        }
                    }
                }
                if ((lane & 3) == 0) {
#pragma unroll
                    for (int mt = 0; mt < 3; mt++) {
                        sm.red[w][0][mt * 16 + r4] = acc[mt][0];
                        sm.red[w][1][mt * 16 + r4] = acc[mt][1];
                        sm.red[w][0][mt * 16 + r4 + 8] = acc[mt][2];
                        sm.red[w][1][mt * 16 + r4 + 8] = acc[mt][3];
                    }
                }
                bar_sync(1, 128);
                if (t < 96) {
                    const int bb = t >= 48, k = t - bb * 48;
                    float h = 0.f;
                    if (k < 36) {
                        const int kk = k + (c & 1) * 4;
                        h = bf_round(sm.red[0][bb][kk] + sm.red[1][bb][kk] + sm.red[2][bb][kk] + sm.red[3][bb][kk]);
                        h = fmaxf(bf_round(h + bf_lo(bias_raw)), 0.f);
                    }
                    reinterpret_cast<__nv_bfloat16*>(sm.hs)[t] = __float2bfloat16_rn(h * h);
                }
                bar_sync(1, 128);
            }
            float acc[9][4] = {};
            {
                uint32_t hb[6];
#pragma unroll
                for (int ks = 0; ks < 3; ks++) { hb[2 * ks] = sm.hs[r4 & 1][ks * 8 + (lane & 3)]; hb[2 * ks + 1] = sm.hs[r4 & 1][ks * 8 + 4 + (lane & 3)]; }
#pragma unroll
                for (int j = 0; j < 3; j++) {
                    if (pass) wait_full(sm, I_W2 + j);
#pragma unroll
                    for (int i = 0; i < 3; i++) {
                        const int mt = w * 3 + i;
#pragma unroll
                        for (int ks = 0; ks < 3; ks++) {
                            const int r = (mt >> 2) * 36 + min(ks * 16 + rowl, 35);
                            uint32_t a[4];
                            ldsm4t(a, ring + ((I_W2 + j) % NST) * SLOT + r * 128 + ((((mt & 3) * 2 + chl) ^ (r & 7)) << 4));
                            mma(acc[j * 3 + i], a[0], a[1], a[2], a[3], hb[2 * ks], hb[2 * ks + 1]);
                        }
                    }
                }
#pragma unroll
                for (int j = 0; j < 9; j++) { acc[j][0] *= 1.f - g0; acc[j][1] *= 1.f - g1; acc[j][2] *= 1.f - g0; acc[j][3] *= 1.f - g1; }
            }
            if (t == 0) TS(3);
            if (pass) mbar_wait(s2u(&sm.obar), 0);
            if (t == 0) TS(9);
            const int bb = r4 & 1;
            float f[4];
            {
                float2 ml[4];
#pragma unroll
                for (int s = 0; s < 4; s++) ml[s] = *reinterpret_cast<const float2*>(&sm.obuf[bb * 4 + s][32]);
                const float M = fmaxf(fmaxf(ml[0].x, ml[1].x), fmaxf(ml[2].x, ml[3].x));
                float L = 0.f;
#pragma unroll
                for (int s = 0; s < 4; s++) { f[s] = ex2((ml[s].x - M) * SC); L = fmaf(f[s], ml[s].y, L); }
                const float inv = (bb ? g1 : g0) * rcp(L);
#pragma unroll
                for (int s = 0; s < 4; s++) f[s] *= inv;
            }
            uint32_t ob[4];
#pragma unroll
            for (int k = 0; k < 4; k++) {
                float o0 = 0.f, o1 = 0.f;
#pragma unroll
                for (int s = 0; s < 4; s++) {
                    const float2 v = *reinterpret_cast<const float2*>(&sm.obuf[bb * 4 + s][k * 8 + (lane & 3) * 2]);
                    o0 = fmaf(f[s], v.x, o0);
                    o1 = fmaf(f[s], v.y, o1);
                }
                ob[k] = pack_bf16(o0, o1);
            }
            const uint32_t ptag = pass ? tag : tag ^ 2u;
            const int jq = lane & 3;
            float* dst = scr->fin + ((size_t)((w * 6 + jq) * 2 + (r4 >> 2)) * NCTA + c) * 8 + (r4 & 3) * 2;
#pragma unroll
            for (int j = 0; j < 3; j++) {
                if (pass) wait_full(sm, I_WO + j);
#pragma unroll
                for (int i = 0; i < 3; i++) {
                    const int mt = w * 3 + i;
#pragma unroll
                    for (int ks = 0; ks < 2; ks++) {
                        const int r = (mt >> 2) * 32 + ks * 16 + rowl;
                        uint32_t a[4];
                        ldsm4t(a, ring + ((I_WO + j) % NST) * SLOT + r * 128 + ((((mt & 3) * 2 + chl) ^ (r & 7)) << 4));
                        mma(acc[j * 3 + i], a[0], a[1], a[2], a[3], ob[2 * ks], ob[2 * ks + 1]);
                    }
                }
                if (j == 2 && t == 0) TS(4);
                const float* a0 = acc[j * 3];
                const float* a1 = acc[j * 3 + 1];
                const float* a2 = acc[j * 3 + 2];
                const float u0 = (jq & 1) ? a0[2] : a0[0], u1 = (jq & 1) ? a0[3] : a0[1];
                const float v0 = (jq & 1) ? a1[2] : a1[0], v1 = (jq & 1) ? a1[3] : a1[1];
                st_msg2(dst + (size_t)j * 48 * NCTA * 8, (jq & 2) ? v0 : u0, (jq & 2) ? v1 : u1, ptag);
                if (jq < 2) st_msg2(dst + (size_t)(j * 48 + 8) * NCTA * 8, (jq & 1) ? a2[2] : a2[0], (jq & 1) ? a2[3] : a2[1], ptag);
            }
            if (t == 0) TS(5);
        }
        return;
    }

    gate(sm, lane, g0, g1);
#pragma unroll 1
    for (int pass = 0; pass < npass; pass++) {
        float o[8][4] = {};
        float m = -INFINITY, l = 0.f;
        if (pass) {
            const float* qp = scr->q + ((c >> 2) & 1) * 4096 + (c >> 3) * 256 + t * 2;
            uint2 v;
            int it = 0;
            do { v = ld_msg2(qp); } while (!ok2(v, tag) && ++it < SPIN_LIMIT);
            (&sm.qs[0][0])[t] = pack_bf16(__uint_as_float(v.x), __uint_as_float(v.y));
            bar_sync(3, 128);
            if (t == 0) TS(6);
            uint32_t qf[16];
#pragma unroll
            for (int ks = 0; ks < 8; ks++) {
                qf[2 * ks] = lane < 8 ? sm.qs[lane >> 2][ks * 8 + (lane & 3)] : 0u;
                qf[2 * ks + 1] = lane < 8 ? sm.qs[lane >> 2][ks * 8 + 4 + (lane & 3)] : 0u;
            }
            const int key = w * 16 + rowl;
            const uint32_t off = key * 128;
            const int sw = key & 7;
#pragma unroll 1
            for (int tl = 0; tl < 16; tl++) {
                const int ik = I_KV + 2 * tl, iv = ik + 1;
                wait_full(sm, ik);
                const uint32_t kb = ring + (ik % NST) * SLOT + off;
                float s[2][2][4] = {};
#pragma unroll
                for (int ks = 0; ks < 8; ks++) {
                    uint32_t kf[4];
                    ldsm4(kf, kb + (ks >> 2) * 8192 + ((((ks & 3) * 2 + chl) ^ sw) << 4));
                    mma(s[0][ks & 1], qf[2 * ks], 0u, qf[2 * ks + 1], 0u, kf[0], kf[1]);
                    mma(s[1][ks & 1], qf[2 * ks], 0u, qf[2 * ks + 1], 0u, kf[2], kf[3]);
                }
                __syncwarp();
                if (lane == 0) release(sm, ik);
                const float s0 = s[0][0][0] + s[0][1][0], s1 = s[0][0][1] + s[0][1][1];
                const float s2 = s[1][0][0] + s[1][1][0], s3 = s[1][0][1] + s[1][1][1];
                float mx = fmaxf(fmaxf(s0, s1), fmaxf(s2, s3));
                mx = fmaxf(mx, __shfl_xor_sync(~0u, mx, 1));
                mx = fmaxf(mx, __shfl_xor_sync(~0u, mx, 2));
                const float mn = fmaxf(m, mx);
                const float al = ex2((m - mn) * SC);
                m = mn;
                const float ms = mn * SC;
                const uint32_t p0 = pack_bf16(ex2(fmaf(s0, SC, -ms)), ex2(fmaf(s1, SC, -ms)));
                const uint32_t p1 = pack_bf16(ex2(fmaf(s2, SC, -ms)), ex2(fmaf(s3, SC, -ms)));
                l = fmaf(l, al, (bf_lo(p0) + bf_hi(p0)) + (bf_lo(p1) + bf_hi(p1)));
                const float a0 = __shfl_sync(~0u, al, 0), a1 = __shfl_sync(~0u, al, 4);
                if (a0 != 1.f || a1 != 1.f) {
#pragma unroll
                    for (int mt = 0; mt < 8; mt++) { o[mt][0] *= a0; o[mt][1] *= a1; o[mt][2] *= a0; o[mt][3] *= a1; }
                }
                wait_full(sm, iv);
                const uint32_t vb = ring + (iv % NST) * SLOT + off;
#pragma unroll
                for (int mt = 0; mt < 8; mt++) {
                    uint32_t vf[4];
                    ldsm4t(vf, vb + (mt >> 2) * 8192 + ((((mt & 3) * 2 + chl) ^ sw) << 4));
                    mma(o[mt], vf[0], vf[1], vf[2], vf[3], p0, p1);
                }
                __syncwarp();
                if (lane == 0) release(sm, iv);
            }
        }
        if (t == 0) TS(7);
        l += __shfl_xor_sync(~0u, l, 1);
        l += __shfl_xor_sync(~0u, l, 2);
        if (lane == 0 || lane == 4) { sm.ml[w][lane >> 2][0] = m; sm.ml[w][lane >> 2][1] = l; }
        if ((lane & 3) == 0) {
#pragma unroll
            for (int mt = 0; mt < 8; mt++) {
                sm.ocomb[w][0][mt * 16 + r4] = o[mt][0];
                sm.ocomb[w][1][mt * 16 + r4] = o[mt][1];
                sm.ocomb[w][0][mt * 16 + r4 + 8] = o[mt][2];
                sm.ocomb[w][1][mt * 16 + r4 + 8] = o[mt][3];
            }
        }
        bar_sync(3, 128);
        const uint32_t ptag = pass ? tag : tag ^ 2u;
        {
            const int h = t >> 6, d = (t & 63) * 2;
            const float M = fmaxf(fmaxf(sm.ml[0][h][0], sm.ml[1][h][0]), fmaxf(sm.ml[2][h][0], sm.ml[3][h][0]));
            float L = 0.f, O0 = 0.f, O1 = 0.f;
#pragma unroll
            for (int k = 0; k < 4; k++) {
                const float sc = ex2((sm.ml[k][h][0] - M) * SC);
                const float2 ov = *reinterpret_cast<const float2*>(&sm.ocomb[k][h][d]);
                L = fmaf(sc, sm.ml[k][h][1], L);
                O0 = fmaf(sc, ov.x, O0);
                O1 = fmaf(sc, ov.y, O1);
            }
            const int dr = t >> 4;
            float* dst = scr->o + ((size_t)((c & ~7) + dr) * 8 + rank) * 40;
            st_msg2(dst + (d & 31), O0, O1, ptag);
            if ((d & 31) < 8) st_msg2(dst + 32 + (d & 31), M, L, ptag);
            const float* src = scr->o + ((size_t)c * 8 + dr) * 40;
            uint2 v = make_uint2(tag ^ pass, tag), ml = make_uint2(tag ^ (pass && (d & 31) == 0), tag);
            int it = 0;
            do {
                ld_msg2_if(v, src + (d & 31), !ok2(v, tag));
                ld_msg2_if(ml, src + 32, !ok2(ml, tag));
            } while (!(ok2(v, tag) && ok2(ml, tag)) && ++it < SPIN_LIMIT);
            if (pass) {
                *reinterpret_cast<uint2*>(&sm.obuf[dr][d & 31]) = v;
                if ((d & 31) == 0) *reinterpret_cast<uint2*>(&sm.obuf[dr][32]) = ml;
                mbar_arrive(s2u(&sm.obar));
            }
        }
        if (t == 0) TS(8);

        if (rid < NRED) {
            if (pass) wait_full(sm, I_POLL);
            const float* src = scr->fin + (size_t)rid * NCTA * 8 + lane * 4;
            uint4 v[8] = {};
            uint32_t need = pass ? 0xffu : 0u;
            int it = 0;
            do {
#pragma unroll
                for (int i = 0; i < 8; i++) ld_msg4_if(v[i], src + i * 128, need & (1u << i));
#pragma unroll
                for (int i = 0; i < 8; i++) if (ok4(v[i], tag)) need &= ~(1u << i);
            } while (__any_sync(~0u, need & (need - 1)) && ++it < SPIN_LIMIT);
            const uint32_t mask = __ballot_sync(~0u, need);
            src += __shfl_sync(~0u, (__ffs(need) - 1) * 128 + lane * 4, need ? lane : __ffs(mask) - 1) - lane * 4;
            uint4 pp[NP] = {};
            float r0 = 0.f, r1 = 0.f, r2 = 0.f, r3 = 0.f;
#pragma unroll
            for (int i = 0; i < NP; i++) ld_msg4_if(pp[i], src, mask);
#pragma unroll
            for (int i = 0; i < 8; i++)
                if (!(need >> i & 1)) { r0 += __uint_as_float(v[i].x); r1 += __uint_as_float(v[i].y); r2 += __uint_as_float(v[i].z); r3 += __uint_as_float(v[i].w); }
            bool more = true;
            do {
#pragma unroll
                for (int i = 0; i < NP; i++) {
                    if ((need != 0) & ok4(pp[i], tag)) { r0 += __uint_as_float(pp[i].x); r1 += __uint_as_float(pp[i].y); r2 += __uint_as_float(pp[i].z); r3 += __uint_as_float(pp[i].w); need = 0; }
                    more = __any_sync(~0u, need);
                    if (!more) break;
                    pp[i] = ld_msg4(src);
                }
            } while (more && ++it < SPIN_LIMIT);
            const bool hi = lane & 16;
            const float t0 = __shfl_xor_sync(~0u, hi ? r0 : r1, 16), t1 = __shfl_xor_sync(~0u, hi ? r2 : r3, 16);
            r0 = (hi ? r1 : r0) + t0;
            r1 = (hi ? r3 : r2) + t1;
            const bool hi2 = lane & 8;
            const float t2 = __shfl_xor_sync(~0u, hi2 ? r0 : r1, 8);
            r0 = (hi2 ? r1 : r0) + t2;
            r0 += __shfl_xor_sync(~0u, r0, 4);
            r0 += __shfl_xor_sync(~0u, r0, 2);
            r0 = fmaf(hi ? 1.f - g1 : 1.f - g0, bf_lo(bias_raw), r0);
            if (pass && (lane & 6) == 0) out[(lane >> 4) * D_MODEL + rid * 4 + (lane & 1) * 2 + ((lane >> 3) & 1)] = __float2bfloat16_rn(r0);
            if (t == 0) TS(10);
        }
    }
    if (c == 0 && t == 0) scr->epoch = epoch + 1u;
}

typedef CUresult (*EncFn)(CUtensorMap*, CUtensorMapDataType, cuuint32_t, void*, const cuuint64_t*, const cuuint64_t*,
                          const cuuint32_t*, const cuuint32_t*, CUtensorMapInterleave, CUtensorMapSwizzle,
                          CUtensorMapL2promotion, CUtensorMapFloatOOBfill);

}

extern "C" void kernel_launch(void* const* d_in, const int* in_sizes, int n_in, void* d_out, int out_size) {
    (void)in_sizes; (void)n_in; (void)out_size;
    EncFn enc = nullptr;
    cudaDriverEntryPointQueryResult qr;
    cudaGetDriverEntryPoint("cuTensorMapEncodeTiled", (void**)&enc, cudaEnableDefault, &qr);
    CUtensorMap mK, mV, mWq, mW1, mW2, mWo;
    const CUtensorMapL2promotion pr = CU_TENSOR_MAP_L2_PROMOTION_L2_256B;
    auto mk3 = [&](CUtensorMap* m, void* p, uint64_t rows, uint64_t rowbytes, uint32_t nblk, uint32_t brows, uint32_t bblk) {
        cuuint64_t d[3] = {64, rows, nblk}, s[2] = {rowbytes, 128};
        cuuint32_t b[3] = {64, brows, bblk}, e[3] = {1, 1, 1};
        enc(m, CU_TENSOR_MAP_DATA_TYPE_BFLOAT16, 3, p, d, s, b, e, CU_TENSOR_MAP_INTERLEAVE_NONE, CU_TENSOR_MAP_SWIZZLE_128B, pr,
            CU_TENSOR_MAP_FLOAT_OOB_FILL_NONE);
    };
    auto mk2 = [&](CUtensorMap* m, void* p, uint64_t cols, uint32_t bcols, CUtensorMapSwizzle sw) {
        cuuint64_t d[2] = {cols, 576}, s[1] = {cols * 2};
        cuuint32_t b[2] = {bcols, 192}, e[2] = {1, 1};
        enc(m, CU_TENSOR_MAP_DATA_TYPE_BFLOAT16, 2, p, d, s, b, e, CU_TENSOR_MAP_INTERLEAVE_NONE, sw, pr,
            CU_TENSOR_MAP_FLOAT_OOB_FILL_NONE);
    };
    mk3(&mK, d_in[1], 32ull * SK, 256, 2, 64, 2);
    mk3(&mV, d_in[2], 32ull * SK, 256, 2, 64, 2);
    mk2(&mWq, d_in[3], 4096, 32, CU_TENSOR_MAP_SWIZZLE_64B);
    mk2(&mW1, d_in[6], 4608, 40, CU_TENSOR_MAP_SWIZZLE_NONE);
    mk3(&mW2, d_in[8], 4608, 1152, 9, 36, 3);
    mk3(&mWo, d_in[4], 4096, 1152, 9, 32, 3);
    const int smem = NST * SLOT + 1024;
    cudaFuncSetAttribute(fused_kernel, cudaFuncAttributeMaxDynamicSharedMemorySize, smem);
    void* scr = nullptr;
    cudaGetSymbolAddress(&scr, g_scr);
    fused_kernel<<<NCTA, 288, smem, cudaStreamPerThread>>>(
        mWq, mK, mV, mW1, mW2, mWo, (const __nv_bfloat16*)d_in[0], (const __nv_bfloat16*)d_in[7], (const __nv_bfloat16*)d_in[9],
        (const __nv_bfloat16*)d_in[10], (__nv_bfloat16*)d_out, (Scratch*)scr);
}
```

```cpp
#include <cuda_runtime.h>
#include <cuda_bf16.h>
#include <cuda.h>
#include <stdint.h>

namespace {

constexpr int D_MODEL = 576;
constexpr int SK = 32768;
constexpr int WIN = 4096;
constexpr int NCTA = 128;
constexpr int NRED = 144;
constexpr int SLOT = 16384;
#define NST 12
#define INFL 4
constexpr int I_KV = 3, I_W1 = 35, I_W2 = 38, I_WO = 41, NITEM = 44;
#define PASS0 0
#define TMPF0 0
#define FTH 0
#define FNS 200
#define ONS 0
#define I_POLL 41
constexpr int SPIN_LIMIT = 1 << 17;

struct Scratch {
    float fin[NRED * NCTA * 8];
    float o[NCTA * 8 * 40];
    float q[2 * 4096];
    unsigned epoch, pad[3];
};
__device__ __align__(128) Scratch g_scr;
#define TS(i) do {} while (0)

struct __align__(16) Smem {
    uint4 tab[NITEM][2];
    uint64_t full[NST + 9];
    uint64_t empty[NST];
    uint64_t obar[1 + ((NST * 2 + 10) & 1)];
    uint32_t xs[2 * 288];
    uint32_t gw[288];
    uint32_t ep[4];
    float red[4][2][48];
    float ocomb[4][2][128];
    float ml[4][2][2];
    float obuf[8][40];
    uint32_t qs[2][64];
    uint32_t hs[2][24];
};

__device__ __forceinline__ uint32_t s2u(const void* p) { return (uint32_t)__cvta_generic_to_shared(p); }
__device__ __forceinline__ void mbar_init(uint32_t a, int c) { asm volatile("mbarrier.init.shared.b64 [%0], %1;" ::"r"(a), "r"(c) : "memory"); }
__device__ __forceinline__ void mbar_expect(uint32_t a, uint32_t b) { asm volatile("mbarrier.arrive.expect_tx.shared.b64 _, [%0], %1;" ::"r"(a), "r"(b) : "memory"); }
__device__ __forceinline__ void mbar_arrive(uint32_t a) { asm volatile("mbarrier.arrive.shared.b64 _, [%0];" ::"r"(a) : "memory"); }
__device__ __forceinline__ void mbar_wait(uint32_t a, uint32_t ph) {
    uint32_t ok;
    int it = 0;
    do {
        asm volatile("{\n.reg .pred p;\nmbarrier.try_wait.parity.shared.b64 p, [%1], %2;\nselp.u32 %0, 1, 0, p;\n}" : "=r"(ok) : "r"(a), "r"(ph) : "memory");
    } while (!ok && ++it < SPIN_LIMIT);
}
__device__ __forceinline__ void tma2d(uint32_t dst, const CUtensorMap* m, int c0, int c1, uint32_t bar) {
    asm volatile("cp.async.bulk.tensor.2d.shared::cluster.global.mbarrier::complete_tx::bytes [%0], [%1, {%3, %4}], [%2];" ::"r"(dst), "l"(m), "r"(bar), "r"(c0), "r"(c1) : "memory");
}
__device__ __forceinline__ void tma3d_ef(uint32_t dst, const CUtensorMap* m, int c0, int c1, int c2, uint32_t bar, uint64_t pol) {
    asm volatile("cp.async.bulk.tensor.3d.shared::cluster.global.mbarrier::complete_tx::bytes.L2::cache_hint [%0], [%1, {%3, %4, %5}], [%2], %6;"
                 ::"r"(dst), "l"(m), "r"(bar), "r"(c0), "r"(c1), "r"(c2), "l"(pol) : "memory");
}
__device__ __forceinline__ void bulk(uint32_t dst, const void* src, uint32_t bytes, uint32_t bar) {
    asm volatile("cp.async.bulk.shared::cluster.global.mbarrier::complete_tx::bytes [%0], [%1], %2, [%3];" ::"r"(dst), "l"(src), "r"(bytes), "r"(bar) : "memory");
}
__device__ __forceinline__ void ldsm4(uint32_t* r, uint32_t a) {
    asm volatile("ldmatrix.sync.aligned.m8n8.x4.shared.b16 {%0,%1,%2,%3}, [%4];" : "=r"(r[0]), "=r"(r[1]), "=r"(r[2]), "=r"(r[3]) : "r"(a) : "memory");
}
__device__ __forceinline__ void ldsm4t(uint32_t* r, uint32_t a) {
    asm volatile("ldmatrix.sync.aligned.m8n8.x4.trans.shared.b16 {%0,%1,%2,%3}, [%4];" : "=r"(r[0]), "=r"(r[1]), "=r"(r[2]), "=r"(r[3]) : "r"(a) : "memory");
}
__device__ __forceinline__ void mma(float* c, uint32_t a0, uint32_t a1, uint32_t a2, uint32_t a3, uint32_t b0, uint32_t b1) {
    asm volatile("mma.sync.aligned.m16n8k16.row.col.f32.bf16.bf16.f32 {%0,%1,%2,%3}, {%4,%5,%6,%7}, {%8,%9}, {%0,%1,%2,%3};"
                 : "+f"(c[0]), "+f"(c[1]), "+f"(c[2]), "+f"(c[3]) : "r"(a0), "r"(a1), "r"(a2), "r"(a3), "r"(b0), "r"(b1));
}
__device__ __forceinline__ uint32_t pack_bf16(float lo, float hi) {
    uint32_t r;
    asm("cvt.rn.bf16x2.f32 %0, %1, %2;" : "=r"(r) : "f"(hi), "f"(lo));
    return r;
}
__device__ __forceinline__ float bf_lo(uint32_t v) { return __uint_as_float(v << 16); }
__device__ __forceinline__ float bf_hi(uint32_t v) { return __uint_as_float(v & 0xffff0000u); }
__device__ __forceinline__ float bf_round(float v) { return __bfloat162float(__float2bfloat16_rn(v)); }
__device__ __forceinline__ float ex2(float v) { float r; asm("ex2.approx.ftz.f32 %0, %1;" : "=f"(r) : "f"(v)); return r; }
__device__ __forceinline__ float rcp(float v) { float r; asm("rcp.approx.ftz.f32 %0, %1;" : "=f"(r) : "f"(v)); return r; }
__device__ __forceinline__ uint32_t ldg32(const void* p) {
    uint32_t v;
    asm volatile("ld.global.nc.u32 %0, [%1];" : "=r"(v) : "l"(p));
    return v;
}
__device__ __forceinline__ uint32_t ldg16(const void* p) {
    uint32_t v;
    asm volatile("ld.global.nc.u16 %0, [%1];" : "=r"(v) : "l"(p));
    return v;
}
__device__ __forceinline__ uint32_t tagw(float v, uint32_t tag) { return (__float_as_uint(v) & ~3u) | tag; }
__device__ __forceinline__ void st_msg2(float* p, float a, float b, uint32_t tag) {
    asm volatile("st.volatile.global.v2.u32 [%0], {%1,%2};" ::"l"(p), "r"(tagw(a, tag)), "r"(tagw(b, tag)) : "memory");
}
__device__ __forceinline__ void st_msg2p(float* p, float a, float b, uint32_t tag, int pass) {
    st_msg2(p, a, b, tag);
}
__device__ __forceinline__ uint2 ld_msg2(const float* p) {
    uint2 v;
    asm volatile("ld.volatile.global.v2.u32 {%0,%1}, [%2];" : "=r"(v.x), "=r"(v.y) : "l"(p) : "memory");
    return v;
}
__device__ __forceinline__ void ld_msg2_if(uint2& v, const float* p, bool pred) {
    asm volatile("{\n.reg .pred p;\nsetp.ne.u32 p, %3, 0;\n@p ld.volatile.global.v2.u32 {%0,%1}, [%2];\n}"
                 : "+r"(v.x), "+r"(v.y) : "l"(p), "r"((uint32_t)pred) : "memory");
}
__device__ __forceinline__ void ld_msg4_if(uint4& v, const float* p, uint32_t pred) {
    asm volatile("{\n.reg .pred p;\nsetp.ne.u32 p, %5, 0;\n@p ld.volatile.global.v4.u32 {%0,%1,%2,%3}, [%4];\n}"
                 : "+r"(v.x), "+r"(v.y), "+r"(v.z), "+r"(v.w) : "l"(p), "r"((uint32_t)pred) : "memory");
}
__device__ __forceinline__ uint4 ld_msg4(const float* p) {
    uint4 v;
    asm volatile("ld.volatile.global.v4.u32 {%0,%1,%2,%3}, [%4];" : "=r"(v.x), "=r"(v.y), "=r"(v.z), "=r"(v.w) : "l"(p) : "memory");
    return v;
}
__device__ __forceinline__ bool ok2(uint2 v, uint32_t tag) { return (((v.x ^ tag) | (v.y ^ tag)) & 3u) == 0; }
__device__ __forceinline__ bool ok4(uint4 v, uint32_t tag) { return (((v.x ^ tag) | (v.y ^ tag) | (v.z ^ tag) | (v.w ^ tag)) & 3u) == 0; }
__device__ __forceinline__ void bar_sync(int id, int n) { asm volatile("bar.sync %0, %1;" ::"r"(id), "r"(n) : "memory"); }
__device__ __forceinline__ uint32_t full_bar(Smem& sm, int i) { return s2u(&sm.full[i < I_W1 ? i % NST : NST + i - I_W1]); }
__device__ __forceinline__ void wait_full(Smem& sm, int i) { mbar_wait(full_bar(sm, i), i < I_W1 ? (i / NST) & 1 : 0); }
__device__ __forceinline__ void release(Smem& sm, int i) { mbar_arrive(s2u(&sm.empty[i % NST])); }

__device__ __forceinline__ void gate(const Smem& sm, int lane, float& g0, float& g1) {
    float s0 = 0.f, s1 = 0.f;
#pragma unroll
    for (int i = 0; i < 9; i++) {
        const uint32_t gv = sm.gw[i * 32 + lane], a = sm.xs[i * 32 + lane], b = sm.xs[288 + i * 32 + lane];
        s0 = fmaf(bf_lo(gv), bf_lo(a), fmaf(bf_hi(gv), bf_hi(a), s0));
        s1 = fmaf(bf_lo(gv), bf_lo(b), fmaf(bf_hi(gv), bf_hi(b), s1));
    }
#pragma unroll
    for (int o = 16; o; o >>= 1) { s0 += __shfl_xor_sync(~0u, s0, o); s1 += __shfl_xor_sync(~0u, s1, o); }
    g0 = 1.f / (1.f + __expf(-s0));
    g1 = 1.f / (1.f + __expf(-s1));
}

struct Maps { CUtensorMap m[6]; };

__global__ void __launch_bounds__(288, 1)
fused_kernel(const char* __restrict__ wq, const __nv_bfloat16* __restrict__ x, const __nv_bfloat16* __restrict__ b1,
             const __nv_bfloat16* __restrict__ b2, const __nv_bfloat16* __restrict__ gate_w,
             __nv_bfloat16* __restrict__ out, Scratch* __restrict__ scr, const __grid_constant__ Maps maps) {
    extern __shared__ __align__(1024) unsigned char smem_raw[];
    __shared__ Smem sm;
    asm volatile("{\n.reg .pred p;\n.reg .b32 t;\n.reg .b64 a;\nmov.u32 t, %%ctaid.x;\nmad.wide.u32 a, t, 36864, %0;\n"
                 "mov.u32 t, %%tid.x;\nsetp.eq.u32 p, t, 0;\n@p cp.async.bulk.prefetch.L2.global [a], 36864;\n}" ::"l"(wq) : "memory");
    const uint32_t ring = (s2u(smem_raw) + 1023u) & ~1023u;
    const int tid = threadIdx.x, lane = tid & 31;
    const int c = blockIdx.x;
    const int warp = __shfl_sync(~0u, tid >> 5, 0);

    if (tid == 0) {
        TS(0);
#pragma unroll
        for (int i = TMPF0; i < 6; i++) asm volatile("prefetch.tensormap [%0];" ::"l"(&maps.m[i]) : "memory");
#pragma unroll
        for (int i = 0; i < NST + 9; i++) mbar_init(s2u(&sm.full[i]), 1);
#pragma unroll
        for (int i = 0; i < NST; i++) mbar_init(s2u(&sm.empty[i]), 4);
        mbar_init(s2u(sm.obar), 128);
        asm volatile("fence.proxy.async.shared::cta;" ::: "memory");
    }
    if (tid < NITEM) {
        const int i = tid;
        const bool q = i < I_KV, kv = !q && i < I_W1, w1 = i >= I_W1 && i < I_W2, wo = i >= I_WO, w2o = i >= I_W2;
        const int k = i - (q ? 0 : kv ? I_KV : w1 ? I_W1 : wo ? I_WO : I_W2);
        const int col = c * (q || wo ? 32 : 36);
        const int kvrow = ((((c >> 2) & 1) * 16 + (c >> 3)) * SK) + (SK - WIN) + (c & 3) * 64;
        const uint32_t c0 = q || w1 ? col & ~7 : 0, c1 = kv ? kvrow + (k >> 1) * 256 : w2o ? col : k * 192, c2 = w2o ? k * 3 : 0;
        const uint32_t bytes = kv ? 16384 : w1 ? 192 * 80 : q || wo ? 32 * 384 : 36 * 384;
        const uint32_t map = q ? 0 : kv ? 1 + (k & 1) : w1 ? 3 : wo ? 5 : 4;
        const int j = i - INFL;
        const int lap = (i >= NST) + (i >= 2 * NST) + (i >= 3 * NST), slot = i - lap * NST;
        const int jl = (j >= NST) + (j >= 2 * NST), js = j < 0 ? NST - 1 : j < I_W1 ? j - jl * NST : NST + j - I_W1;
        const uint32_t fl = (j < 0 ? 1 : j < I_W1 ? jl & 1 : 0) | ((~lap & 1) << 1) | (map << 10);
        const uint32_t bars = s2u(sm.full);
        sm.tab[i][0] = make_uint4(ring + slot * SLOT, bars + (i < I_W1 ? slot : NST + i - I_W1) * 8, c0, c1);
        sm.tab[i][1] = make_uint4(c2, bytes, bars + js * 8, fl | ((bars + (NST + 9 + slot) * 8) << 16));
    }
    int warp2;
    asm volatile("mov.u32 %0, %1;" : "=r"(warp2) : "r"(warp));
    if (warp2 == 0) {
        asm volatile("bar.arrive 0, 288;" ::: "memory");
        __syncwarp();
        if (lane != 0) return;
        {
            TS(13);
            uint64_t pol;
            asm volatile("createpolicy.fractional.L2::evict_first.b64 %0, 1.0;" : "=l"(pol));
#pragma unroll 1
            for (int i = 0; i < NITEM; i++) {
                const uint4 a = sm.tab[i][0], b = sm.tab[i][1];
                const char* map = reinterpret_cast<const char*>(&maps) + ((b.w >> 3) & 0x380);
                asm volatile("" : "+l"(map));
                mbar_wait(b.w >> 16, (b.w >> 1) & 1);
                mbar_expect(a.y, b.y);
                mbar_wait(b.z, b.w & 1);
                tma3d_ef(a.x, reinterpret_cast<const CUtensorMap*>(map), a.z, a.w, b.x, a.y, pol);
            }
            TS(1);
        }
    }
    if (warp == 0) return;

    uint32_t xf[18], bias_raw = 0;
    const int t = (tid - 32) & 127, w = (warp - 1) & 3;
    const int rid = w * NCTA + c;
    {
        const int l = tid - 32;
        const void* src = l < 144 ? (const void*)(x + l * 8) : l < 216 ? (const void*)(gate_w + (l - 144) * 8) : (const void*)&scr->epoch;
        if (l <= 216) {
            uint4 v;
            asm volatile("ld.volatile.global.v4.u32 {%0,%1,%2,%3}, [%4];" : "=r"(v.x), "=r"(v.y), "=r"(v.z), "=r"(v.w) : "l"(src));
            reinterpret_cast<uint4*>(sm.xs)[l] = v;
        }
    }
    if (warp > 4) {
        const int k = t % 48;
        if (k < 36) bias_raw = ldg16(b1 + c * 36 + k);
    } else if (rid < NRED) {
        bias_raw = ldg16(b2 + rid * 4 + (lane & 1) * 2 + ((lane >> 3) & 1));
    }
    bar_sync(0, 288);
    const uint32_t epoch = sm.ep[0];
    if (warp > 4) {
        const uint32_t* xp = sm.xs + ((lane >> 2) & 1) * 288 + w * 24 + (lane & 3);
#pragma unroll
        for (int j = 0; j < 9; j++) { xf[j * 2] = xp[j / 3 * 96 + j % 3 * 8]; xf[j * 2 + 1] = xp[j / 3 * 96 + j % 3 * 8 + 4]; }
    }

    const uint32_t tag = (epoch + 1u) & 3u;
    const int rowl = ((lane >> 4) << 3) + (lane & 7);
    const int chl = (lane >> 3) & 1;
    const float SC = 0.08838834764831845f * 1.4426950408889634f;
    const int rank = c & 7, r4 = lane >> 2;
    float g0, g1;
    int npass;
    asm volatile("mov.u32 %0, 2;" : "=r"(npass));

    if (warp > 4) {
        if (t == 0) TS(14);
        {
            float acc[2][4] = {};
#pragma unroll
            for (int j = 0; j < 3; j++) {
                wait_full(sm, j);
#pragma unroll
                for (int i = 0; i < 3; i++) {
                    const int r = (w * 3 + i) * 16 + rowl;
#pragma unroll
                    for (int mt = 0; mt < 2; mt++) {
                        uint32_t a[4];
                        ldsm4t(a, ring + j * SLOT + r * 64 + (((mt * 2 + chl) ^ ((r >> 1) & 3)) << 4));
                        mma(acc[mt], a[0], a[1], a[2], a[3], xf[(j * 3 + i) * 2], xf[(j * 3 + i) * 2 + 1]);
                    }
                }
                __syncwarp();
                if (lane == 0) release(sm, j);
            }
            if ((lane & 3) == 0) {
#pragma unroll
                for (int mt = 0; mt < 2; mt++) {
                    sm.red[w][0][mt * 16 + r4] = acc[mt][0];
                    sm.red[w][1][mt * 16 + r4] = acc[mt][1];
                    sm.red[w][0][mt * 16 + r4 + 8] = acc[mt][2];
                    sm.red[w][1][mt * 16 + r4 + 8] = acc[mt][3];
                }
            }
            bar_sync(1, 128);
            if (t < 32) {
                const int bq = t >> 4, p = t & 15;
                float q0 = 0.f, q1 = 0.f;
#pragma unroll
                for (int k = 0; k < 4; k++) { const float2 v = *reinterpret_cast<const float2*>(&sm.red[k][bq][p * 2]); q0 += v.x; q1 += v.y; }
                st_msg2(&scr->q[bq * 4096 + c * 32 + p * 2], q0, q1, tag);
            }
            if (t == 0) TS(2);
            bar_sync(1, 128);
        }
        gate(sm, lane, g0, g1);
#pragma unroll 1
        for (int pass = PASS0; pass < npass; pass++) {
            {
                float acc[3][4] = {};
#pragma unroll
                for (int j = 0; j < 3; j++) {
                    if (pass) wait_full(sm, I_W1 + j);
#pragma unroll
                    for (int i = 0; i < 3; i++) {
                        const uint32_t base = ring + ((I_W1 + j) % NST) * SLOT + ((w * 3 + i) * 16 + rowl) * 80 + chl * 16;
#pragma unroll
                        for (int mt = 0; mt < 3; mt++) {
                            uint32_t a[4];
                            ldsm4t(a, base + mt * 32);
                            mma(acc[mt], a[0], a[1], a[2], a[3], xf[(j * 3 + i) * 2], xf[(j * 3 + i) * 2 + 1]);
                        }
                    }
                }
                if ((lane & 3) == 0) {
#pragma unroll
                    for (int mt = 0; mt < 3; mt++) {
                        sm.red[w][0][mt * 16 + r4] = acc[mt][0];
                        sm.red[w][1][mt * 16 + r4] = acc[mt][1];
                        sm.red[w][0][mt * 16 + r4 + 8] = acc[mt][2];
                        sm.red[w][1][mt * 16 + r4 + 8] = acc[mt][3];
                    }
                }
                bar_sync(1, 128);
                if (t < 96) {
                    const int bb = t >= 48, k = t - bb * 48;
                    float h = 0.f;
                    if (k < 36) {
                        const int kk = k + (c & 1) * 4;
                        h = bf_round(sm.red[0][bb][kk] + sm.red[1][bb][kk] + sm.red[2][bb][kk] + sm.red[3][bb][kk]);
                        h = fmaxf(bf_round(h + bf_lo(bias_raw)), 0.f);
                    }
                    reinterpret_cast<__nv_bfloat16*>(sm.hs)[t] = __float2bfloat16_rn(h * h);
                }
                bar_sync(1, 128);
            }
            float acc[9][4] = {};
            {
                uint32_t hb[6];
#pragma unroll
                for (int ks = 0; ks < 3; ks++) { hb[2 * ks] = sm.hs[r4 & 1][ks * 8 + (lane & 3)]; hb[2 * ks + 1] = sm.hs[r4 & 1][ks * 8 + 4 + (lane & 3)]; }
#pragma unroll
                for (int j = 0; j < 3; j++) {
                    if (pass) wait_full(sm, I_W2 + j);
#pragma unroll
                    for (int i = 0; i < 3; i++) {
                        const int mt = w * 3 + i;
#pragma unroll
                        for (int ks = 0; ks < 3; ks++) {
                            const int r = (mt >> 2) * 36 + min(ks * 16 + rowl, 35);
                            uint32_t a[4];
                            ldsm4t(a, ring + ((I_W2 + j) % NST) * SLOT + r * 128 + ((((mt & 3) * 2 + chl) ^ (r & 7)) << 4));
                            mma(acc[j * 3 + i], a[0], a[1], a[2], a[3], hb[2 * ks], hb[2 * ks + 1]);
                        }
                    }
                }
#pragma unroll
                for (int j = 0; j < 9; j++) { acc[j][0] *= 1.f - g0; acc[j][1] *= 1.f - g1; acc[j][2] *= 1.f - g0; acc[j][3] *= 1.f - g1; }
            }
            if (t == 0) TS(3);
            if (pass) mbar_wait(s2u(sm.obar), 0);
            if (t == 0) TS(9);
            const int bb = r4 & 1;
            float f[4];
            {
                float2 ml[4];
#pragma unroll
                for (int s = 0; s < 4; s++) ml[s] = *reinterpret_cast<const float2*>(&sm.obuf[bb * 4 + s][32]);
                const float M = fmaxf(fmaxf(ml[0].x, ml[1].x), fmaxf(ml[2].x, ml[3].x));
                float L = 0.f;
#pragma unroll
                for (int s = 0; s < 4; s++) { f[s] = ex2((ml[s].x - M) * SC); L = fmaf(f[s], ml[s].y, L); }
                const float inv = (bb ? g1 : g0) * rcp(L);
#pragma unroll
                for (int s = 0; s < 4; s++) f[s] *= inv;
            }
            uint32_t ob[4];
#pragma unroll
            for (int k = 0; k < 4; k++) {
                float o0 = 0.f, o1 = 0.f;
#pragma unroll
                for (int s = 0; s < 4; s++) {
                    const float2 v = *reinterpret_cast<const float2*>(&sm.obuf[bb * 4 + s][k * 8 + (lane & 3) * 2]);
                    o0 = fmaf(f[s], v.x, o0);
                    o1 = fmaf(f[s], v.y, o1);
                }
                ob[k] = pack_bf16(o0, o1);
            }
            const uint32_t ptag = pass ? tag : tag ^ 2u;
            const int jq = lane & 3;
            float* dst = scr->fin + ((size_t)((w * 6 + jq) * 2 + (r4 >> 2)) * NCTA + c) * 8 + (r4 & 3) * 2;
#pragma unroll
            for (int j = 0; j < 3; j++) {
                if (pass) wait_full(sm, I_WO + j);
#pragma unroll
                for (int i = 0; i < 3; i++) {
                    const int mt = w * 3 + i;
#pragma unroll
                    for (int ks = 0; ks < 2; ks++) {
                        const int r = (mt >> 2) * 32 + ks * 16 + rowl;
                        uint32_t a[4];
                        ldsm4t(a, ring + ((I_WO + j) % NST) * SLOT + r * 128 + ((((mt & 3) * 2 + chl) ^ (r & 7)) << 4));
                        mma(acc[j * 3 + i], a[0], a[1], a[2], a[3], ob[2 * ks], ob[2 * ks + 1]);
                    }
                }
                if (j == 2 && t == 0) TS(4);
                const float* a0 = acc[j * 3];
                const float* a1 = acc[j * 3 + 1];
                const float* a2 = acc[j * 3 + 2];
                const float u0 = (jq & 1) ? a0[2] : a0[0], u1 = (jq & 1) ? a0[3] : a0[1];
                const float v0 = (jq & 1) ? a1[2] : a1[0], v1 = (jq & 1) ? a1[3] : a1[1];
                st_msg2p(dst + (size_t)j * 48 * NCTA * 8, (jq & 2) ? v0 : u0, (jq & 2) ? v1 : u1, ptag, pass);
                if (jq < 2) st_msg2p(dst + (size_t)(j * 48 + 8) * NCTA * 8, (jq & 1) ? a2[2] : a2[0], (jq & 1) ? a2[3] : a2[1], ptag, pass);
            }
            if (t == 0) TS(5);
        }
        return;
    }

    gate(sm, lane, g0, g1);
#pragma unroll 1
    for (int pass = PASS0; pass < npass; pass++) {
        float o[8][4] = {};
        float m = -INFINITY, l = 0.f;
        if (pass) {
            const float* qp = scr->q + ((c >> 2) & 1) * 4096 + (c >> 3) * 256 + t * 2;
            uint2 v;
            int it = 0;
            do { v = ld_msg2(qp); } while (!ok2(v, tag) && ++it < SPIN_LIMIT);
            (&sm.qs[0][0])[t] = pack_bf16(__uint_as_float(v.x), __uint_as_float(v.y));
            bar_sync(3, 128);
            if (t == 0) TS(6);
            uint32_t qf[16];
#pragma unroll
            for (int ks = 0; ks < 8; ks++) {
                qf[2 * ks] = lane < 8 ? sm.qs[lane >> 2][ks * 8 + (lane & 3)] : 0u;
                qf[2 * ks + 1] = lane < 8 ? sm.qs[lane >> 2][ks * 8 + 4 + (lane & 3)] : 0u;
            }
            const int key = w * 16 + rowl;
            const uint32_t off = key * 128;
            const int sw = key & 7;
#pragma unroll 1
            for (int tl = 0; tl < 16; tl++) {
                const int ik = I_KV + 2 * tl, iv = ik + 1;
                wait_full(sm, ik);
                const uint32_t kb = ring + (ik % NST) * SLOT + off;
                float s[2][2][4] = {};
#pragma unroll
                for (int ks = 0; ks < 8; ks++) {
                    uint32_t kf[4];
                    ldsm4(kf, kb + (ks >> 2) * 8192 + ((((ks & 3) * 2 + chl) ^ sw) << 4));
                    mma(s[0][ks & 1], qf[2 * ks], 0u, qf[2 * ks + 1], 0u, kf[0], kf[1]);
                    mma(s[1][ks & 1], qf[2 * ks], 0u, qf[2 * ks + 1], 0u, kf[2], kf[3]);
                }
                __syncwarp();
                if (lane == 0) release(sm, ik);
                const float s0 = s[0][0][0] + s[0][1][0], s1 = s[0][0][1] + s[0][1][1];
                const float s2 = s[1][0][0] + s[1][1][0], s3 = s[1][0][1] + s[1][1][1];
                float mx = fmaxf(fmaxf(s0, s1), fmaxf(s2, s3));
                mx = fmaxf(mx, __shfl_xor_sync(~0u, mx, 1));
                mx = fmaxf(mx, __shfl_xor_sync(~0u, mx, 2));
                const float mn = fmaxf(m, mx);
                const float al = ex2((m - mn) * SC);
                m = mn;
                const float ms = mn * SC;
                const uint32_t p0 = pack_bf16(ex2(fmaf(s0, SC, -ms)), ex2(fmaf(s1, SC, -ms)));
                const uint32_t p1 = pack_bf16(ex2(fmaf(s2, SC, -ms)), ex2(fmaf(s3, SC, -ms)));
                l = fmaf(l, al, (bf_lo(p0) + bf_hi(p0)) + (bf_lo(p1) + bf_hi(p1)));
                const float a0 = __shfl_sync(~0u, al, 0), a1 = __shfl_sync(~0u, al, 4);
                if (a0 != 1.f || a1 != 1.f) {
#pragma unroll
                    for (int mt = 0; mt < 8; mt++) { o[mt][0] *= a0; o[mt][1] *= a1; o[mt][2] *= a0; o[mt][3] *= a1; }
                }
                wait_full(sm, iv);
                const uint32_t vb = ring + (iv % NST) * SLOT + off;
#pragma unroll
                for (int mt = 0; mt < 8; mt++) {
                    uint32_t vf[4];
                    ldsm4t(vf, vb + (mt >> 2) * 8192 + ((((mt & 3) * 2 + chl) ^ sw) << 4));
                    mma(o[mt], vf[0], vf[1], vf[2], vf[3], p0, p1);
                }
                __syncwarp();
                if (lane == 0) release(sm, iv);
            }
        }
        if (t == 0) TS(7);
        l += __shfl_xor_sync(~0u, l, 1);
        l += __shfl_xor_sync(~0u, l, 2);
        if (lane == 0 || lane == 4) { sm.ml[w][lane >> 2][0] = m; sm.ml[w][lane >> 2][1] = l; }
        if ((lane & 3) == 0) {
#pragma unroll
            for (int mt = 0; mt < 8; mt++) {
                sm.ocomb[w][0][mt * 16 + r4] = o[mt][0];
                sm.ocomb[w][1][mt * 16 + r4] = o[mt][1];
                sm.ocomb[w][0][mt * 16 + r4 + 8] = o[mt][2];
                sm.ocomb[w][1][mt * 16 + r4 + 8] = o[mt][3];
            }
        }
        bar_sync(3, 128);
        const uint32_t ptag = pass ? tag : tag ^ 2u;
        {
            const int h = t >> 6, d = (t & 63) * 2;
            const float M = fmaxf(fmaxf(sm.ml[0][h][0], sm.ml[1][h][0]), fmaxf(sm.ml[2][h][0], sm.ml[3][h][0]));
            float L = 0.f, O0 = 0.f, O1 = 0.f;
#pragma unroll
            for (int k = 0; k < 4; k++) {
                const float sc = ex2((sm.ml[k][h][0] - M) * SC);
                const float2 ov = *reinterpret_cast<const float2*>(&sm.ocomb[k][h][d]);
                L = fmaf(sc, sm.ml[k][h][1], L);
                O0 = fmaf(sc, ov.x, O0);
                O1 = fmaf(sc, ov.y, O1);
            }
            const int dr = t >> 4;
            float* dst = scr->o + ((size_t)((c & ~7) + dr) * 8 + rank) * 40;
            st_msg2p(dst + (d & 31), O0, O1, ptag, pass);
            if ((d & 31) < 8) st_msg2p(dst + 32 + (d & 31), M, L, ptag, pass);
            const float* src = scr->o + ((size_t)c * 8 + dr) * 40;
            uint2 v = make_uint2(tag ^ pass, tag), ml = make_uint2(tag ^ (pass && (d & 31) == 0), tag);
            int it = 0;
            do {
                ld_msg2_if(v, src + (d & 31), !ok2(v, tag));
                ld_msg2_if(ml, src + 32, !ok2(ml, tag));
            } while (!(ok2(v, tag) && ok2(ml, tag)) && ++it < SPIN_LIMIT);
            if (pass) {
                *reinterpret_cast<uint2*>(&sm.obuf[dr][d & 31]) = v;
                if ((d & 31) == 0) *reinterpret_cast<uint2*>(&sm.obuf[dr][32]) = ml;
                mbar_arrive(s2u(sm.obar));
            }
        }
        if (t == 0) TS(8);

        if (rid < NRED) {
            if (pass) wait_full(sm, I_POLL);
            const float* src = scr->fin + (size_t)rid * NCTA * 8 + lane * 4;
            uint4 v[8] = {};
            uint32_t need = pass ? 0xffu : 0u;
            int it = 0, miss;
            do {
#pragma unroll
                for (int i = 0; i < 8; i++) ld_msg4_if(v[i], src + i * 128, need & (1u << i));
#pragma unroll
                for (int i = 0; i < 8; i++) if (ok4(v[i], tag)) need &= ~(1u << i);
                miss = __reduce_add_sync(~0u, __popc(need));
            } while (miss && ++it < SPIN_LIMIT);
            float r0 = 0.f, r1 = 0.f, r2 = 0.f, r3 = 0.f;
#pragma unroll
            for (int i = 0; i < 8; i++) { r0 += __uint_as_float(v[i].x); r1 += __uint_as_float(v[i].y); r2 += __uint_as_float(v[i].z); r3 += __uint_as_float(v[i].w); }
            const bool hi = lane & 16;
            const float t0 = __shfl_xor_sync(~0u, hi ? r0 : r1, 16), t1 = __shfl_xor_sync(~0u, hi ? r2 : r3, 16);
            r0 = (hi ? r1 : r0) + t0;
            r1 = (hi ? r3 : r2) + t1;
            const bool hi2 = lane & 8;
            const float t2 = __shfl_xor_sync(~0u, hi2 ? r0 : r1, 8);
            r0 = (hi2 ? r1 : r0) + t2;
            r0 += __shfl_xor_sync(~0u, r0, 4);
            r0 += __shfl_xor_sync(~0u, r0, 2);
            r0 = fmaf(hi ? 1.f - g1 : 1.f - g0, bf_lo(bias_raw), r0);
            if (pass && (lane & 6) == 0) out[(lane >> 4) * D_MODEL + rid * 4 + (lane & 1) * 2 + ((lane >> 3) & 1)] = __float2bfloat16_rn(r0);
            if (t == 0) TS(10);
        }
    }
    if (c == 0 && t == 0) scr->epoch = epoch + 1u;
}

typedef CUresult (*EncFn)(CUtensorMap*, CUtensorMapDataType, cuuint32_t, void*, const cuuint64_t*, const cuuint64_t*,
                          const cuuint32_t*, const cuuint32_t*, CUtensorMapInterleave, CUtensorMapSwizzle,
                          CUtensorMapL2promotion, CUtensorMapFloatOOBfill);

}

extern "C" void kernel_launch(void* const* d_in, const int* in_sizes, int n_in, void* d_out, int out_size) {
    (void)in_sizes; (void)n_in; (void)out_size;
    EncFn enc = nullptr;
    cudaDriverEntryPointQueryResult qr;
    cudaGetDriverEntryPoint("cuTensorMapEncodeTiled", (void**)&enc, cudaEnableDefault, &qr);
    Maps maps;
    const CUtensorMapL2promotion pr = CU_TENSOR_MAP_L2_PROMOTION_L2_256B;
    auto mk = [&](int i, void* p, uint64_t d0, uint64_t d1, uint64_t d2, uint64_t s1, uint64_t s2, uint32_t b0, uint32_t b1, uint32_t b2,
                  CUtensorMapSwizzle sw) {
        cuuint64_t d[3] = {d0, d1, d2}, s[2] = {s1, s2};
        cuuint32_t b[3] = {b0, b1, b2}, e[3] = {1, 1, 1};
        enc(&maps.m[i], CU_TENSOR_MAP_DATA_TYPE_BFLOAT16, 3, p, d, s, b, e, CU_TENSOR_MAP_INTERLEAVE_NONE, sw, pr,
            CU_TENSOR_MAP_FLOAT_OOB_FILL_NONE);
    };
    mk(0, d_in[3], 4096, 576, 1, 8192, 8192 * 576, 32, 192, 1, CU_TENSOR_MAP_SWIZZLE_64B);
    mk(1, d_in[1], 64, 32ull * SK, 2, 256, 128, 64, 64, 2, CU_TENSOR_MAP_SWIZZLE_128B);
    mk(2, d_in[2], 64, 32ull * SK, 2, 256, 128, 64, 64, 2, CU_TENSOR_MAP_SWIZZLE_128B);
    mk(3, d_in[6], 4608, 576, 1, 9216, 9216 * 576, 40, 192, 1, CU_TENSOR_MAP_SWIZZLE_NONE);
    mk(4, d_in[8], 64, 4608, 9, 1152, 128, 64, 36, 3, CU_TENSOR_MAP_SWIZZLE_128B);
    mk(5, d_in[4], 64, 4096, 9, 1152, 128, 64, 32, 3, CU_TENSOR_MAP_SWIZZLE_128B);
    const int smem = NST * SLOT + 1024;
    cudaFuncSetAttribute(fused_kernel, cudaFuncAttributeMaxDynamicSharedMemorySize, smem);
    void* scr = nullptr;
    cudaGetSymbolAddress(&scr, g_scr);
    fused_kernel<<<NCTA, 288, smem, cudaStreamPerThread>>>(
        (const char*)d_in[3], (const __nv_bfloat16*)d_in[0], (const __nv_bfloat16*)d_in[7], (const __nv_bfloat16*)d_in[9],
        (const __nv_bfloat16*)d_in[10], (__nv_bfloat16*)d_out, (Scratch*)scr, maps);
}
```

```cpp
#include <cuda_runtime.h>
#include <cuda_bf16.h>
#include <cuda.h>
#include <stdint.h>

namespace {

constexpr int D_MODEL = 576;
constexpr int SK = 32768;
constexpr int WIN = 4096;
constexpr int NCTA = 128;
constexpr int SLOT = 16384;
constexpr int NST = 12;
constexpr int INFL = 4;
constexpr int I_KV = 3, I_W1 = 35, I_W2 = 38, I_WO = 41, NITEM = 44;
constexpr int RDY_TL = 9;
constexpr int I_QPOLL = 5;
constexpr int ACC_PITCH = 16;
constexpr int SPIN_LIMIT = 1 << 17;

struct Scratch {
    float acc[192 * ACC_PITCH];
    float o[NCTA * 8 * 40];
    float q[2 * 4096];
    unsigned ready, pad[3];
};
__device__ __align__(128) Scratch g_scr;

struct __align__(16) Smem {
    uint4 tab[NITEM][2];
    uint64_t full[NST + 9];
    uint64_t empty[NST];
    uint64_t obar[1 + ((NST * 2 + 10) & 1)];
    uint32_t xs[2 * 288];
    uint32_t gw[288];
    uint32_t ep[4];
    float red[4][2][48];
    float ocomb[4][2][128];
    float ml[4][2][2];
    float obuf[8][40];
    uint32_t qs[2][64];
    uint32_t hs[2][24];
};

__device__ __forceinline__ uint32_t s2u(const void* p) { return (uint32_t)__cvta_generic_to_shared(p); }
__device__ __forceinline__ void mbar_init(uint32_t a, int c) { asm volatile("mbarrier.init.shared.b64 [%0], %1;" ::"r"(a), "r"(c) : "memory"); }
__device__ __forceinline__ void mbar_expect(uint32_t a, uint32_t b) { asm volatile("mbarrier.arrive.expect_tx.shared.b64 _, [%0], %1;" ::"r"(a), "r"(b) : "memory"); }
__device__ __forceinline__ void mbar_arrive(uint32_t a) { asm volatile("mbarrier.arrive.shared.b64 _, [%0];" ::"r"(a) : "memory"); }
__device__ __forceinline__ void mbar_wait(uint32_t a, uint32_t ph) {
    uint32_t ok;
    int it = 0;
    do {
        asm volatile("{\n.reg .pred p;\nmbarrier.try_wait.parity.shared.b64 p, [%1], %2;\nselp.u32 %0, 1, 0, p;\n}" : "=r"(ok) : "r"(a), "r"(ph) : "memory");
    } while (!ok && ++it < SPIN_LIMIT);
}
__device__ __forceinline__ void tma3d_ef(uint32_t dst, const CUtensorMap* m, int c0, int c1, int c2, uint32_t bar, uint64_t pol) {
    asm volatile("cp.async.bulk.tensor.3d.shared::cluster.global.mbarrier::complete_tx::bytes.L2::cache_hint [%0], [%1, {%3, %4, %5}], [%2], %6;"
                 ::"r"(dst), "l"(m), "r"(bar), "r"(c0), "r"(c1), "r"(c2), "l"(pol) : "memory");
}
__device__ __forceinline__ void ldsm4(uint32_t* r, uint32_t a) {
    asm volatile("ldmatrix.sync.aligned.m8n8.x4.shared.b16 {%0,%1,%2,%3}, [%4];" : "=r"(r[0]), "=r"(r[1]), "=r"(r[2]), "=r"(r[3]) : "r"(a) : "memory");
}
__device__ __forceinline__ void ldsm4t(uint32_t* r, uint32_t a) {
    asm volatile("ldmatrix.sync.aligned.m8n8.x4.trans.shared.b16 {%0,%1,%2,%3}, [%4];" : "=r"(r[0]), "=r"(r[1]), "=r"(r[2]), "=r"(r[3]) : "r"(a) : "memory");
}
__device__ __forceinline__ void mma(float* c, uint32_t a0, uint32_t a1, uint32_t a2, uint32_t a3, uint32_t b0, uint32_t b1) {
    asm volatile("mma.sync.aligned.m16n8k16.row.col.f32.bf16.bf16.f32 {%0,%1,%2,%3}, {%4,%5,%6,%7}, {%8,%9}, {%0,%1,%2,%3};"
                 : "+f"(c[0]), "+f"(c[1]), "+f"(c[2]), "+f"(c[3]) : "r"(a0), "r"(a1), "r"(a2), "r"(a3), "r"(b0), "r"(b1));
}
__device__ __forceinline__ uint32_t pack_bf16(float lo, float hi) {
    uint32_t r;
    asm("cvt.rn.bf16x2.f32 %0, %1, %2;" : "=r"(r) : "f"(hi), "f"(lo));
    return r;
}
__device__ __forceinline__ float bf_lo(uint32_t v) { return __uint_as_float(v << 16); }
__device__ __forceinline__ float bf_hi(uint32_t v) { return __uint_as_float(v & 0xffff0000u); }
__device__ __forceinline__ float bf_round(float v) { return __bfloat162float(__float2bfloat16_rn(v)); }
__device__ __forceinline__ float ex2(float v) { float r; asm("ex2.approx.ftz.f32 %0, %1;" : "=f"(r) : "f"(v)); return r; }
__device__ __forceinline__ float rcp(float v) { float r; asm("rcp.approx.ftz.f32 %0, %1;" : "=f"(r) : "f"(v)); return r; }
__device__ __forceinline__ uint32_t ldg16(const void* p) {
    uint32_t v;
    asm volatile("ld.global.nc.u16 %0, [%1];" : "=r"(v) : "l"(p));
    return v;
}
__device__ __forceinline__ uint32_t tagw(float v, uint32_t tag) { return (__float_as_uint(v) & ~3u) | tag; }
__device__ __forceinline__ void st_msg2(float* p, float a, float b, uint32_t tag) {
    asm volatile("st.relaxed.gpu.global.v2.u32 [%0], {%1,%2};" ::"l"(p), "r"(tagw(a, tag)), "r"(tagw(b, tag)) : "memory");
}
__device__ __forceinline__ void st_zero4(float* p) {
    asm volatile("st.relaxed.gpu.global.v4.u32 [%0], {%1,%1,%1,%1};" ::"l"(p), "r"(0u) : "memory");
}
__device__ __forceinline__ void st_val2_if(float* p, float a, float b, uint32_t pred) {
    asm volatile("{\n.reg .pred p;\nsetp.ne.u32 p, %3, 0;\n@p st.relaxed.gpu.global.v2.u32 [%0], {%1,%2};\n}"
                 ::"l"(p), "r"(__float_as_uint(a) | 1u), "r"(__float_as_uint(b) | 1u), "r"(pred) : "memory");
}
__device__ __forceinline__ uint2 ld_msg2(const float* p) {
    uint2 v;
    asm volatile("ld.relaxed.gpu.global.v2.u32 {%0,%1}, [%2];" : "=r"(v.x), "=r"(v.y) : "l"(p) : "memory");
    return v;
}
__device__ __forceinline__ void ld_msg2_if(uint2& v, const float* p, bool pred) {
    asm volatile("{\n.reg .pred p;\nsetp.ne.u32 p, %3, 0;\n@p ld.relaxed.gpu.global.v2.u32 {%0,%1}, [%2];\n}"
                 : "+r"(v.x), "+r"(v.y) : "l"(p), "r"((uint32_t)pred) : "memory");
}
__device__ __forceinline__ bool ok2(uint2 v, uint32_t tag) { return (((v.x ^ tag) | (v.y ^ tag)) & 3u) == 0; }
__device__ __forceinline__ bool val2(uint2 v) { return v.x & v.y & 1u; }
__device__ __forceinline__ void bar_sync(int id, int n) { asm volatile("bar.sync %0, %1;" ::"r"(id), "r"(n) : "memory"); }
__device__ __forceinline__ uint32_t full_bar(Smem& sm, int i) { return s2u(&sm.full[i < I_W1 ? i % NST : NST + i - I_W1]); }
__device__ __forceinline__ void wait_full(Smem& sm, int i) { mbar_wait(full_bar(sm, i), i < I_W1 ? (i / NST) & 1 : 0); }
__device__ __forceinline__ void release(Smem& sm, int i) { mbar_arrive(s2u(&sm.empty[i % NST])); }

__device__ __forceinline__ void gate(const Smem& sm, int lane, float& g0, float& g1) {
    float s0 = 0.f, s1 = 0.f;
#pragma unroll
    for (int i = 0; i < 9; i++) {
        const uint32_t gv = sm.gw[i * 32 + lane], a = sm.xs[i * 32 + lane], b = sm.xs[288 + i * 32 + lane];
        s0 = fmaf(bf_lo(gv), bf_lo(a), fmaf(bf_hi(gv), bf_hi(a), s0));
        s1 = fmaf(bf_lo(gv), bf_lo(b), fmaf(bf_hi(gv), bf_hi(b), s1));
    }
#pragma unroll
    for (int o = 16; o; o >>= 1) { s0 += __shfl_xor_sync(~0u, s0, o); s1 += __shfl_xor_sync(~0u, s1, o); }
    g0 = 1.f / (1.f + __expf(-s0));
    g1 = 1.f / (1.f + __expf(-s1));
}

struct Maps { CUtensorMap m[6]; };

__global__ void __launch_bounds__(288, 1)
fused_kernel(const char* __restrict__ wq, const __nv_bfloat16* __restrict__ x, const __nv_bfloat16* __restrict__ b1,
             const __nv_bfloat16* __restrict__ b2, const __nv_bfloat16* __restrict__ gate_w,
             __nv_bfloat16* __restrict__ out, Scratch* __restrict__ scr, const __grid_constant__ Maps maps) {
    extern __shared__ __align__(1024) unsigned char smem_raw[];
    __shared__ Smem sm;
    asm volatile("{\n.reg .pred p;\n.reg .b32 t;\n.reg .b64 a;\nmov.u32 t, %%ctaid.x;\nmad.wide.u32 a, t, 36864, %0;\n"
                 "mov.u32 t, %%tid.x;\nsetp.eq.u32 p, t, 0;\n@p cp.async.bulk.prefetch.L2.global [a], 36864;\n}" ::"l"(wq) : "memory");
    const uint32_t ring = (s2u(smem_raw) + 1023u) & ~1023u;
    const int tid = threadIdx.x, lane = tid & 31;
    const int c = blockIdx.x;
    const int warp = __shfl_sync(~0u, tid >> 5, 0);

    if (tid == 0) {
#pragma unroll
        for (int i = 0; i < 6; i++) asm volatile("prefetch.tensormap [%0];" ::"l"(&maps.m[i]) : "memory");
#pragma unroll
        for (int i = 0; i < NST + 9; i++) mbar_init(s2u(&sm.full[i]), 1);
#pragma unroll
        for (int i = 0; i < NST; i++) mbar_init(s2u(&sm.empty[i]), 4);
        mbar_init(s2u(sm.obar), 128);
        asm volatile("fence.proxy.async.shared::cta;" ::: "memory");
    }
    if (tid < NITEM) {
        const int i = tid;
        const bool q = i < I_KV, kv = !q && i < I_W1, w1 = i >= I_W1 && i < I_W2, wo = i >= I_WO, w2o = i >= I_W2;
        const int k = i - (q ? 0 : kv ? I_KV : w1 ? I_W1 : wo ? I_WO : I_W2);
        const int col = c * (q || wo ? 32 : 36);
        const int kvrow = ((((c >> 2) & 1) * 16 + (c >> 3)) * SK) + (SK - WIN) + (c & 3) * 64;
        const uint32_t c0 = q || w1 ? col & ~7 : 0, c1 = kv ? kvrow + (k >> 1) * 256 : w2o ? col : k * 192, c2 = w2o ? (k + c) % 3 * 3 : 0;
        const uint32_t bytes = kv ? 16384 : w1 ? 192 * 80 : q || wo ? 32 * 384 : 36 * 384;
        const uint32_t map = q ? 0 : kv ? 1 + (k & 1) : w1 ? 3 : wo ? 5 : 4;
        const int j = i - INFL;
        const int lap = (i >= NST) + (i >= 2 * NST) + (i >= 3 * NST), slot = i - lap * NST;
        const int jl = (j >= NST) + (j >= 2 * NST), js = j < 0 ? NST - 1 : j < I_W1 ? j - jl * NST : NST + j - I_W1;
        const uint32_t fl = (j < 0 ? 1 : j < I_W1 ? jl & 1 : 0) | ((~lap & 1) << 1) | (map << 10);
        const uint32_t bars = s2u(sm.full);
        sm.tab[i][0] = make_uint4(ring + slot * SLOT, bars + (i < I_W1 ? slot : NST + i - I_W1) * 8, c0, c1);
        sm.tab[i][1] = make_uint4(c2, bytes, bars + js * 8, fl | ((bars + (NST + 9 + slot) * 8) << 16));
    }
    int warp2;
    asm volatile("mov.u32 %0, %1;" : "=r"(warp2) : "r"(warp));
    if (warp2 == 0) {
        asm volatile("bar.arrive 0, 288;" ::: "memory");
        __syncwarp();
        if (lane != 0) return;
        {
            uint64_t pol;
            asm volatile("createpolicy.fractional.L2::evict_first.b64 %0, 1.0;" : "=l"(pol));
#pragma unroll 1
            for (int i = 0; i < NITEM; i++) {
                const uint4 a = sm.tab[i][0], b = sm.tab[i][1];
                const char* map = reinterpret_cast<const char*>(&maps) + ((b.w >> 3) & 0x380);
                asm volatile("" : "+l"(map));
                mbar_wait(b.w >> 16, (b.w >> 1) & 1);
                mbar_expect(a.y, b.y);
                mbar_wait(b.z, b.w & 1);
                tma3d_ef(a.x, reinterpret_cast<const CUtensorMap*>(map), a.z, a.w, b.x, a.y, pol);
            }
        }
    }
    if (warp == 0) return;

    uint32_t xf[18], bias_raw = 0;
    const int t = (tid - 32) & 127, w = (warp - 1) & 3;
    {
        const int l = tid - 32;
        const void* src = l < 144 ? (const void*)(x + l * 8) : l < 216 ? (const void*)(gate_w + (l - 144) * 8) : (const void*)&scr->ready;
        if (l <= 216) {
            uint4 v;
            asm volatile("ld.relaxed.gpu.global.v4.u32 {%0,%1,%2,%3}, [%4];" : "=r"(v.x), "=r"(v.y), "=r"(v.z), "=r"(v.w) : "l"(src));
            reinterpret_cast<uint4*>(sm.xs)[l] = v;
        }
    }
    if (warp > 4) {
        const int k = t % 48;
        if (k < 36) bias_raw = ldg16(b1 + c * 36 + k);
    }
    bar_sync(0, 288);
    const uint32_t epoch = sm.ep[0] / NCTA;
    if (warp > 4) {
        const uint32_t* xp = sm.xs + ((lane >> 2) & 1) * 288 + w * 24 + (lane & 3);
#pragma unroll
        for (int j = 0; j < 9; j++) { xf[j * 2] = xp[j / 3 * 96 + j % 3 * 8]; xf[j * 2 + 1] = xp[j / 3 * 96 + j % 3 * 8 + 4]; }
    }

    const uint32_t tag = (epoch + 1u) & 3u;
    const int rowl = ((lane >> 4) << 3) + (lane & 7);
    const int chl = (lane >> 3) & 1;
    const float SC = 0.08838834764831845f * 1.4426950408889634f;
    const int rank = c & 7, r4 = lane >> 2;
    int npass;
    asm volatile("mov.u32 %0, 2;" : "=r"(npass));

    if (warp > 4) {
        {
            float acc[2][4] = {};
#pragma unroll
            for (int j = 0; j < 3; j++) {
                wait_full(sm, j);
#pragma unroll
                for (int i = 0; i < 3; i++) {
                    const int r = (w * 3 + i) * 16 + rowl;
#pragma unroll
                    for (int mt = 0; mt < 2; mt++) {
                        uint32_t a[4];
                        ldsm4t(a, ring + j * SLOT + r * 64 + (((mt * 2 + chl) ^ ((r >> 1) & 3)) << 4));
                        mma(acc[mt], a[0], a[1], a[2], a[3], xf[(j * 3 + i) * 2], xf[(j * 3 + i) * 2 + 1]);
                    }
                }
                __syncwarp();
                if (lane == 0) release(sm, j);
            }
            if ((lane & 3) == 0) {
#pragma unroll
                for (int mt = 0; mt < 2; mt++) {
                    sm.red[w][0][mt * 16 + r4] = acc[mt][0];
                    sm.red[w][1][mt * 16 + r4] = acc[mt][1];
                    sm.red[w][0][mt * 16 + r4 + 8] = acc[mt][2];
                    sm.red[w][1][mt * 16 + r4 + 8] = acc[mt][3];
                }
            }
            bar_sync(1, 128);
            if (t < 32) {
                const int bq = t >> 4, p = t & 15;
                float q0 = 0.f, q1 = 0.f;
#pragma unroll
                for (int k = 0; k < 4; k++) { const float2 v = *reinterpret_cast<const float2*>(&sm.red[k][bq][p * 2]); q0 += v.x; q1 += v.y; }
                st_msg2(&scr->q[bq * 4096 + c * 32 + p * 2], q0, q1, tag);
            }
            bar_sync(1, 128);
        }
        if (t < 80) st_zero4(scr->o + (size_t)c * 320 + t * 4);
        float g0, g1;
        gate(sm, lane, g0, g1);
        const int jq = lane & 3;
        if (c < 3) {
            const float ba = bf_lo(ldg16(b2 + c * 192 + w * 48 + jq * 8 + r4));
            const float bb = bf_lo(ldg16(b2 + c * 192 + w * 48 + 32 + (jq & 1) * 8 + r4));
            asm volatile("st.relaxed.gpu.global.v4.f32 [%0], {%1,%2,%3,%4};"
                         ::"l"(scr->acc + ((c * 128 + t) >> 1) * ACC_PITCH + (t & 1) * 4), "f"((1.f - g0) * ba), "f"((1.f - g1) * ba),
                           "f"((1.f - ((jq & 2) ? g1 : g0)) * bb), "f"(0.f) : "memory");
        }
#pragma unroll 1
        for (int pass = 0; pass < npass; pass++) {
            {
                float acc[3][4] = {};
#pragma unroll
                for (int j = 0; j < 3; j++) {
                    if (pass) wait_full(sm, I_W1 + j);
#pragma unroll
                    for (int i = 0; i < 3; i++) {
                        const uint32_t base = ring + ((I_W1 + j) % NST) * SLOT + ((w * 3 + i) * 16 + rowl) * 80 + chl * 16;
#pragma unroll
                        for (int mt = 0; mt < 3; mt++) {
                            uint32_t a[4];
                            ldsm4t(a, base + mt * 32);
                            mma(acc[mt], a[0], a[1], a[2], a[3], xf[(j * 3 + i) * 2], xf[(j * 3 + i) * 2 + 1]);
                        }
                    }
                }
                if ((lane & 3) == 0) {
#pragma unroll
                    for (int mt = 0; mt < 3; mt++) {
                        sm.red[w][0][mt * 16 + r4] = acc[mt][0];
                        sm.red[w][1][mt * 16 + r4] = acc[mt][1];
                        sm.red[w][0][mt * 16 + r4 + 8] = acc[mt][2];
                        sm.red[w][1][mt * 16 + r4 + 8] = acc[mt][3];
                    }
                }
                bar_sync(1, 128);
                if (t < 96) {
                    const int bb = t >= 48, k = t - bb * 48;
                    float h = 0.f;
                    if (k < 36) {
                        const int kk = k + (c & 1) * 4;
                        h = bf_round(sm.red[0][bb][kk] + sm.red[1][bb][kk] + sm.red[2][bb][kk] + sm.red[3][bb][kk]);
                        h = fmaxf(bf_round(h + bf_lo(bias_raw)), 0.f);
                    }
                    reinterpret_cast<__nv_bfloat16*>(sm.hs)[t] = __float2bfloat16_rn(h * h);
                }
                bar_sync(1, 128);
            }
            float acc[9][4] = {};
            {
                uint32_t hb[6];
#pragma unroll
                for (int ks = 0; ks < 3; ks++) { hb[2 * ks] = sm.hs[r4 & 1][ks * 8 + (lane & 3)]; hb[2 * ks + 1] = sm.hs[r4 & 1][ks * 8 + 4 + (lane & 3)]; }
#pragma unroll
                for (int j = 0; j < 3; j++) {
                    if (pass) wait_full(sm, I_W2 + j);
#pragma unroll
                    for (int i = 0; i < 3; i++) {
                        const int mt = w * 3 + i;
#pragma unroll
                        for (int ks = 0; ks < 3; ks++) {
                            const int r = (mt >> 2) * 36 + min(ks * 16 + rowl, 35);
                            uint32_t a[4];
                            ldsm4t(a, ring + ((I_W2 + j) % NST) * SLOT + r * 128 + ((((mt & 3) * 2 + chl) ^ (r & 7)) << 4));
                            mma(acc[j * 3 + i], a[0], a[1], a[2], a[3], hb[2 * ks], hb[2 * ks + 1]);
                        }
                    }
                }
#pragma unroll
                for (int j = 0; j < 9; j++) { acc[j][0] *= 1.f - g0; acc[j][1] *= 1.f - g1; acc[j][2] *= 1.f - g0; acc[j][3] *= 1.f - g1; }
            }
            if (pass) mbar_wait(s2u(sm.obar), 0);
            const int bb = r4 & 1;
            float f[4];
            {
                float2 ml[4];
#pragma unroll
                for (int s = 0; s < 4; s++) ml[s] = *reinterpret_cast<const float2*>(&sm.obuf[bb * 4 + s][32]);
                const float M = fmaxf(fmaxf(ml[0].x, ml[1].x), fmaxf(ml[2].x, ml[3].x));
                float L = 0.f;
#pragma unroll
                for (int s = 0; s < 4; s++) { f[s] = ex2((ml[s].x - M) * SC); L = fmaf(f[s], ml[s].y, L); }
                const float inv = (bb ? g1 : g0) * rcp(L);
#pragma unroll
                for (int s = 0; s < 4; s++) f[s] *= inv;
            }
            uint32_t ob[4];
#pragma unroll
            for (int k = 0; k < 4; k++) {
                float o0 = 0.f, o1 = 0.f;
#pragma unroll
                for (int s = 0; s < 4; s++) {
                    const float2 v = *reinterpret_cast<const float2*>(&sm.obuf[bb * 4 + s][k * 8 + (lane & 3) * 2]);
                    o0 = fmaf(f[s], v.x, o0);
                    o1 = fmaf(f[s], v.y, o1);
                }
                ob[k] = pack_bf16(o0, o1);
            }
            float fp[3][3], fo[3][4];
#pragma unroll
            for (int j = 0; j < 3; j++) {
                if (pass) wait_full(sm, I_WO + j);
#pragma unroll
                for (int i = 0; i < 3; i++) {
                    const int mt = w * 3 + i;
#pragma unroll
                    for (int ks = 0; ks < 2; ks++) {
                        const int r = (mt >> 2) * 32 + ks * 16 + rowl;
                        uint32_t a[4];
                        ldsm4t(a, ring + ((I_WO + j) % NST) * SLOT + r * 128 + ((((mt & 3) * 2 + chl) ^ (r & 7)) << 4));
                        mma(acc[j * 3 + i], a[0], a[1], a[2], a[3], ob[2 * ks], ob[2 * ks + 1]);
                    }
                }
                const float* a0 = acc[j * 3];
                const float* a1 = acc[j * 3 + 1];
                const float* a2 = acc[j * 3 + 2];
                const float u0 = (jq & 1) ? a0[2] : a0[0], u1 = (jq & 1) ? a0[3] : a0[1];
                const float v0 = (jq & 1) ? a1[2] : a1[0], v1 = (jq & 1) ? a1[3] : a1[1];
                fp[j][0] = (jq & 2) ? v0 : u0;
                fp[j][1] = (jq & 2) ? v1 : u1;
                fp[j][2] = (jq & 1) ? ((jq & 2) ? a2[3] : a2[2]) : ((jq & 2) ? a2[1] : a2[0]);
                fo[j][0] = fo[j][1] = fo[j][2] = fo[j][3] = 0.f;
                asm volatile("{\n.reg .pred p;\nsetp.ne.u32 p, %9, 0;\n@p atom.relaxed.gpu.global.add.v4.f32 {%0,%1,%2,%3}, [%4], {%5,%6,%7,%8};\n}"
                             : "+f"(fo[j][0]), "+f"(fo[j][1]), "+f"(fo[j][2]), "+f"(fo[j][3])
                             : "l"(scr->acc + (((j + c) % 3 * 128 + t) >> 1) * ACC_PITCH + (t & 1) * 4), "f"(fp[j][0]), "f"(fp[j][1]),
                               "f"(fp[j][2]), "f"(1.f), "r"(pass) : "memory");
            }
#pragma unroll
            for (int j = 0; j < 3; j++) {
                const int jr = (j + c) % 3;
                const int e0 = jr * 192 + w * 48 + jq * 8 + r4, e2 = (jq >> 1) * D_MODEL + jr * 192 + w * 48 + 32 + (jq & 1) * 8 + r4;
                const int e[3] = {e0, e0 + D_MODEL, e2};
                if (fo[j][3] == (float)(NCTA - 1)) {
#pragma unroll
                    for (int k = 0; k < 3; k++) out[e[k]] = __float2bfloat16_rn(fo[j][k] + fp[j][k]);
                }
            }
            if (!pass) {
                bar_sync(1, 128);
                if (t == 0) asm volatile("red.release.gpu.global.add.u32 [%0], 1;" ::"l"(&scr->ready) : "memory");
            }
        }
        return;
    }

#pragma unroll 1
    for (int pass = 0; pass < npass; pass++) {
        float o[8][4] = {};
        float m = -INFINITY, l = 0.f;
        if (pass) {
            const float* qp = scr->q + ((c >> 2) & 1) * 4096 + (c >> 3) * 256 + t * 2;
            uint2 v;
            int it = 0;
            wait_full(sm, I_QPOLL);
            do { v = ld_msg2(qp); } while (!ok2(v, tag) && ++it < SPIN_LIMIT);
            (&sm.qs[0][0])[t] = pack_bf16(__uint_as_float(v.x), __uint_as_float(v.y));
            bar_sync(3, 128);
            uint32_t qf[16];
#pragma unroll
            for (int ks = 0; ks < 8; ks++) {
                qf[2 * ks] = lane < 8 ? sm.qs[lane >> 2][ks * 8 + (lane & 3)] : 0u;
                qf[2 * ks + 1] = lane < 8 ? sm.qs[lane >> 2][ks * 8 + 4 + (lane & 3)] : 0u;
            }
            const int key = w * 16 + rowl;
            const uint32_t off = key * 128;
            const int sw = key & 7;
#pragma unroll 1
            for (int tl = 0; tl < 16; tl++) {
                const int ik = I_KV + 2 * tl, iv = ik + 1;
                if (tl == RDY_TL && t == 0) {
                    uint32_t seen;
                    it = 0;
                    do {
                        asm volatile("ld.acquire.gpu.global.u32 %0, [%1];" : "=r"(seen) : "l"(&scr->ready) : "memory");
                    } while ((int)(seen - (epoch + 1u) * NCTA) < 0 && ++it < SPIN_LIMIT);
                }
                wait_full(sm, ik);
                const uint32_t kb = ring + (ik % NST) * SLOT + off;
                float s[2][2][4] = {};
#pragma unroll
                for (int ks = 0; ks < 8; ks++) {
                    uint32_t kf[4];
                    ldsm4(kf, kb + (ks >> 2) * 8192 + ((((ks & 3) * 2 + chl) ^ sw) << 4));
                    mma(s[0][ks & 1], qf[2 * ks], 0u, qf[2 * ks + 1], 0u, kf[0], kf[1]);
                    mma(s[1][ks & 1], qf[2 * ks], 0u, qf[2 * ks + 1], 0u, kf[2], kf[3]);
                }
                __syncwarp();
                if (lane == 0) release(sm, ik);
                const float s0 = s[0][0][0] + s[0][1][0], s1 = s[0][0][1] + s[0][1][1];
                const float s2 = s[1][0][0] + s[1][1][0], s3 = s[1][0][1] + s[1][1][1];
                float mx = fmaxf(fmaxf(s0, s1), fmaxf(s2, s3));
                mx = fmaxf(mx, __shfl_xor_sync(~0u, mx, 1));
                mx = fmaxf(mx, __shfl_xor_sync(~0u, mx, 2));
                const float mn = fmaxf(m, mx);
                const float al = ex2((m - mn) * SC);
                m = mn;
                const float ms = mn * SC;
                const uint32_t p0 = pack_bf16(ex2(fmaf(s0, SC, -ms)), ex2(fmaf(s1, SC, -ms)));
                const uint32_t p1 = pack_bf16(ex2(fmaf(s2, SC, -ms)), ex2(fmaf(s3, SC, -ms)));
                l = fmaf(l, al, (bf_lo(p0) + bf_hi(p0)) + (bf_lo(p1) + bf_hi(p1)));
                const float a0 = __shfl_sync(~0u, al, 0), a1 = __shfl_sync(~0u, al, 4);
                if (a0 != 1.f || a1 != 1.f) {
#pragma unroll
                    for (int mt = 0; mt < 8; mt++) { o[mt][0] *= a0; o[mt][1] *= a1; o[mt][2] *= a0; o[mt][3] *= a1; }
                }
                wait_full(sm, iv);
                const uint32_t vb = ring + (iv % NST) * SLOT + off;
#pragma unroll
                for (int mt = 0; mt < 8; mt++) {
                    uint32_t vf[4];
                    ldsm4t(vf, vb + (mt >> 2) * 8192 + ((((mt & 3) * 2 + chl) ^ sw) << 4));
                    mma(o[mt], vf[0], vf[1], vf[2], vf[3], p0, p1);
                }
                __syncwarp();
                if (lane == 0) release(sm, iv);
            }
        }
        l += __shfl_xor_sync(~0u, l, 1);
        l += __shfl_xor_sync(~0u, l, 2);
        if (lane == 0 || lane == 4) { sm.ml[w][lane >> 2][0] = m; sm.ml[w][lane >> 2][1] = l; }
        if ((lane & 3) == 0) {
#pragma unroll
            for (int mt = 0; mt < 8; mt++) {
                sm.ocomb[w][0][mt * 16 + r4] = o[mt][0];
                sm.ocomb[w][1][mt * 16 + r4] = o[mt][1];
                sm.ocomb[w][0][mt * 16 + r4 + 8] = o[mt][2];
                sm.ocomb[w][1][mt * 16 + r4 + 8] = o[mt][3];
            }
        }
        bar_sync(3, 128);
        {
            const int h = t >> 6, d = (t & 63) * 2;
            const float M = fmaxf(fmaxf(sm.ml[0][h][0], sm.ml[1][h][0]), fmaxf(sm.ml[2][h][0], sm.ml[3][h][0]));
            float L = 0.f, O0 = 0.f, O1 = 0.f;
#pragma unroll
            for (int k = 0; k < 4; k++) {
                const float sc = ex2((sm.ml[k][h][0] - M) * SC);
                const float2 ov = *reinterpret_cast<const float2*>(&sm.ocomb[k][h][d]);
                L = fmaf(sc, sm.ml[k][h][1], L);
                O0 = fmaf(sc, ov.x, O0);
                O1 = fmaf(sc, ov.y, O1);
            }
            const int dr = t >> 4;
            float* dst = scr->o + ((size_t)((c & ~7) + dr) * 8 + rank) * 40;
            st_val2_if(dst + (d & 31), O0, O1, pass);
            st_val2_if(dst + 32 + (d & 31), M, L, pass && (d & 31) < 8);
            const float* src = scr->o + ((size_t)c * 8 + dr) * 40;
            uint2 v = make_uint2(!pass, 1u), ml = make_uint2(!(pass && (d & 31) == 0), 1u);
            int it = 0;
            do {
                ld_msg2_if(v, src + (d & 31), !val2(v));
                ld_msg2_if(ml, src + 32, !val2(ml));
            } while (!(val2(v) && val2(ml)) && ++it < SPIN_LIMIT);
            if (pass) {
                *reinterpret_cast<uint2*>(&sm.obuf[dr][d & 31]) = v;
                if ((d & 31) == 0) *reinterpret_cast<uint2*>(&sm.obuf[dr][32]) = ml;
                mbar_arrive(s2u(sm.obar));
            }
        }
    }
}

typedef CUresult (*EncFn)(CUtensorMap*, CUtensorMapDataType, cuuint32_t, void*, const cuuint64_t*, const cuuint64_t*,
                          const cuuint32_t*, const cuuint32_t*, CUtensorMapInterleave, CUtensorMapSwizzle,
                          CUtensorMapL2promotion, CUtensorMapFloatOOBfill);

}

extern "C" void kernel_launch(void* const* d_in, const int* in_sizes, int n_in, void* d_out, int out_size) {
    (void)in_sizes; (void)n_in; (void)out_size;
    EncFn enc = nullptr;
    cudaDriverEntryPointQueryResult qr;
    cudaGetDriverEntryPoint("cuTensorMapEncodeTiled", (void**)&enc, cudaEnableDefault, &qr);
    Maps maps;
    const CUtensorMapL2promotion pr = CU_TENSOR_MAP_L2_PROMOTION_L2_256B;
    auto mk = [&](int i, void* p, uint64_t d0, uint64_t d1, uint64_t d2, uint64_t s1, uint64_t s2, uint32_t b0, uint32_t b1, uint32_t b2,
                  CUtensorMapSwizzle sw) {
        cuuint64_t d[3] = {d0, d1, d2}, s[2] = {s1, s2};
        cuuint32_t b[3] = {b0, b1, b2}, e[3] = {1, 1, 1};
        enc(&maps.m[i], CU_TENSOR_MAP_DATA_TYPE_BFLOAT16, 3, p, d, s, b, e, CU_TENSOR_MAP_INTERLEAVE_NONE, sw, pr,
            CU_TENSOR_MAP_FLOAT_OOB_FILL_NONE);
    };
    mk(0, d_in[3], 4096, 576, 1, 8192, 8192 * 576, 32, 192, 1, CU_TENSOR_MAP_SWIZZLE_64B);
    mk(1, d_in[1], 64, 32ull * SK, 2, 256, 128, 64, 64, 2, CU_TENSOR_MAP_SWIZZLE_128B);
    mk(2, d_in[2], 64, 32ull * SK, 2, 256, 128, 64, 64, 2, CU_TENSOR_MAP_SWIZZLE_128B);
    mk(3, d_in[6], 4608, 576, 1, 9216, 9216 * 576, 40, 192, 1, CU_TENSOR_MAP_SWIZZLE_NONE);
    mk(4, d_in[8], 64, 4608, 9, 1152, 128, 64, 36, 3, CU_TENSOR_MAP_SWIZZLE_128B);
    mk(5, d_in[4], 64, 4096, 9, 1152, 128, 64, 32, 3, CU_TENSOR_MAP_SWIZZLE_128B);
    const int smem = NST * SLOT + 1024;
    cudaFuncSetAttribute(fused_kernel, cudaFuncAttributeMaxDynamicSharedMemorySize, smem);
    void* scr = nullptr;
    cudaGetSymbolAddress(&scr, g_scr);
    fused_kernel<<<NCTA, 288, smem, cudaStreamPerThread>>>(
        (const char*)d_in[3], (const __nv_bfloat16*)d_in[0], (const __nv_bfloat16*)d_in[7], (const __nv_bfloat16*)d_in[9],
        (const __nv_bfloat16*)d_in[10], (__nv_bfloat16*)d_out, (Scratch*)scr, maps);
}
```

```cpp
#include <cuda_runtime.h>
#include <cuda_bf16.h>
#include <cuda.h>
#include <stdint.h>

namespace {

constexpr int D_MODEL = 576;
constexpr int SK = 32768;
constexpr int WIN = 4096;
constexpr int NCTA = 128;
constexpr int SLOT = 16384;
constexpr int NST = 12;
constexpr int INFL = 4;
constexpr int I_KV = 3, I_W1 = 35, I_W2 = 38, I_WO = 41, NITEM = 45;
constexpr int NTAIL = NITEM - I_W1;
constexpr int NTHR = 352;
constexpr int RDY_TL = 9;
constexpr int I_QPOLL = 5;
constexpr int ACC_PITCH = 16;
constexpr int SPIN_LIMIT = 1 << 17;

struct Scratch {
    float acc[192 * ACC_PITCH];
    float o[NCTA / 2 * 8 * 72];
    float q[2 * 4096];
    unsigned ready, pad[3];
};
__device__ __align__(128) Scratch g_scr;

struct __align__(16) Smem {
    uint4 tab[NITEM][2];
    uint64_t full[NST + NTAIL];
    uint64_t empty[NST];
    uint64_t obar, hbar;
    uint32_t xs[2 * 288];
    uint32_t gw[288];
    uint32_t ep[4];
    float red[6][2][80];
    float hx[144];
    float ocomb[4][2][128];
    float ml[4][2][2];
    uint32_t qs[2][64];
    uint32_t hs[2][36];
    uint32_t os[2][36];
};

__device__ __forceinline__ uint32_t s2u(const void* p) { return (uint32_t)__cvta_generic_to_shared(p); }
__device__ __forceinline__ void mbar_init(uint32_t a, int c) { asm volatile("mbarrier.init.shared.b64 [%0], %1;" ::"r"(a), "r"(c) : "memory"); }
__device__ __forceinline__ void mbar_expect(uint32_t a, uint32_t b) { asm volatile("mbarrier.arrive.expect_tx.shared.b64 _, [%0], %1;" ::"r"(a), "r"(b) : "memory"); }
__device__ __forceinline__ void mbar_arrive(uint32_t a) { asm volatile("mbarrier.arrive.shared.b64 _, [%0];" ::"r"(a) : "memory"); }
__device__ __forceinline__ void mbar_wait(uint32_t a, uint32_t ph) {
    uint32_t ok;
    int it = 0;
    do {
        asm volatile("{\n.reg .pred p;\nmbarrier.try_wait.parity.shared.b64 p, [%1], %2;\nselp.u32 %0, 1, 0, p;\n}" : "=r"(ok) : "r"(a), "r"(ph) : "memory");
    } while (!ok && ++it < SPIN_LIMIT);
}
__device__ __forceinline__ void tma3d_ef(uint32_t dst, const CUtensorMap* m, int c0, int c1, int c2, uint32_t bar, uint64_t pol) {
    asm volatile("cp.async.bulk.tensor.3d.shared::cluster.global.mbarrier::complete_tx::bytes.L2::cache_hint [%0], [%1, {%3, %4, %5}], [%2], %6;"
                 ::"r"(dst), "l"(m), "r"(bar), "r"(c0), "r"(c1), "r"(c2), "l"(pol) : "memory");
}
__device__ __forceinline__ void ldsm4(uint32_t* r, uint32_t a) {
    asm volatile("ldmatrix.sync.aligned.m8n8.x4.shared.b16 {%0,%1,%2,%3}, [%4];" : "=r"(r[0]), "=r"(r[1]), "=r"(r[2]), "=r"(r[3]) : "r"(a) : "memory");
}
__device__ __forceinline__ void ldsm4t(uint32_t* r, uint32_t a) {
    asm volatile("ldmatrix.sync.aligned.m8n8.x4.trans.shared.b16 {%0,%1,%2,%3}, [%4];" : "=r"(r[0]), "=r"(r[1]), "=r"(r[2]), "=r"(r[3]) : "r"(a) : "memory");
}
__device__ __forceinline__ void mma(float* c, uint32_t a0, uint32_t a1, uint32_t a2, uint32_t a3, uint32_t b0, uint32_t b1) {
    asm volatile("mma.sync.aligned.m16n8k16.row.col.f32.bf16.bf16.f32 {%0,%1,%2,%3}, {%4,%5,%6,%7}, {%8,%9}, {%0,%1,%2,%3};"
                 : "+f"(c[0]), "+f"(c[1]), "+f"(c[2]), "+f"(c[3]) : "r"(a0), "r"(a1), "r"(a2), "r"(a3), "r"(b0), "r"(b1));
}
__device__ __forceinline__ uint32_t pack_bf16(float lo, float hi) {
    uint32_t r;
    asm("cvt.rn.bf16x2.f32 %0, %1, %2;" : "=r"(r) : "f"(hi), "f"(lo));
    return r;
}
__device__ __forceinline__ float bf_lo(uint32_t v) { return __uint_as_float(v << 16); }
__device__ __forceinline__ float bf_hi(uint32_t v) { return __uint_as_float(v & 0xffff0000u); }
__device__ __forceinline__ float bf_round(float v) { return __bfloat162float(__float2bfloat16_rn(v)); }
__device__ __forceinline__ float ex2(float v) { float r; asm("ex2.approx.ftz.f32 %0, %1;" : "=f"(r) : "f"(v)); return r; }
__device__ __forceinline__ float rcp(float v) { float r; asm("rcp.approx.ftz.f32 %0, %1;" : "=f"(r) : "f"(v)); return r; }
__device__ __forceinline__ uint32_t ldg16(const void* p) {
    uint32_t v;
    asm volatile("ld.global.nc.u16 %0, [%1];" : "=r"(v) : "l"(p));
    return v;
}
__device__ __forceinline__ uint32_t tagw(float v, uint32_t tag) { return (__float_as_uint(v) & ~3u) | tag; }
__device__ __forceinline__ void st_msg2(float* p, float a, float b, uint32_t tag) {
    asm volatile("st.relaxed.gpu.global.v2.u32 [%0], {%1,%2};" ::"l"(p), "r"(tagw(a, tag)), "r"(tagw(b, tag)) : "memory");
}
__device__ __forceinline__ void st_zero4(float* p) {
    asm volatile("st.relaxed.gpu.global.v4.u32 [%0], {%1,%1,%1,%1};" ::"l"(p), "r"(0u) : "memory");
}
__device__ __forceinline__ void st_val2_if(float* p, float a, float b, uint32_t pred) {
    asm volatile("{\n.reg .pred p;\nsetp.ne.u32 p, %3, 0;\n@p st.relaxed.gpu.global.v2.u32 [%0], {%1,%2};\n}"
                 ::"l"(p), "r"(__float_as_uint(a) | 1u), "r"(__float_as_uint(b) | 1u), "r"(pred) : "memory");
}
__device__ __forceinline__ uint2 ld_msg2(const float* p) {
    uint2 v;
    asm volatile("ld.relaxed.gpu.global.v2.u32 {%0,%1}, [%2];" : "=r"(v.x), "=r"(v.y) : "l"(p) : "memory");
    return v;
}
__device__ __forceinline__ void ld_msg2_if(uint2& v, const float* p, bool pred) {
    asm volatile("{\n.reg .pred p;\nsetp.ne.u32 p, %3, 0;\n@p ld.relaxed.gpu.global.v2.u32 {%0,%1}, [%2];\n}"
                 : "+r"(v.x), "+r"(v.y) : "l"(p), "r"((uint32_t)pred) : "memory");
}
__device__ __forceinline__ void ld_msg4_if(uint4& v, const float* p, bool pred) {
    asm volatile("{\n.reg .pred p;\nsetp.ne.u32 p, %5, 0;\n@p ld.relaxed.gpu.global.v4.u32 {%0,%1,%2,%3}, [%4];\n}"
                 : "+r"(v.x), "+r"(v.y), "+r"(v.z), "+r"(v.w) : "l"(p), "r"((uint32_t)pred) : "memory");
}
__device__ __forceinline__ bool val4(uint4 v) { return v.x & v.y & v.z & v.w & 1u; }
__device__ __forceinline__ bool ok2(uint2 v, uint32_t tag) { return (((v.x ^ tag) | (v.y ^ tag)) & 3u) == 0; }
__device__ __forceinline__ bool val2(uint2 v) { return v.x & v.y & 1u; }
__device__ __forceinline__ void bar_sync(int id, int n) { asm volatile("bar.sync %0, %1;" ::"r"(id), "r"(n) : "memory"); }
__device__ __forceinline__ uint32_t full_bar(Smem& sm, int i) { return s2u(&sm.full[i < I_W1 ? i % NST : NST + i - I_W1]); }
__device__ __forceinline__ void wait_full(Smem& sm, int i) { mbar_wait(full_bar(sm, i), i < I_W1 ? (i / NST) & 1 : 0); }
__device__ __forceinline__ void release(Smem& sm, int i) { mbar_arrive(s2u(&sm.empty[i % NST])); }

__device__ __forceinline__ void gate(const Smem& sm, int lane, float& g0, float& g1) {
    float s0 = 0.f, s1 = 0.f;
#pragma unroll
    for (int i = 0; i < 9; i++) {
        const uint32_t gv = sm.gw[i * 32 + lane], a = sm.xs[i * 32 + lane], b = sm.xs[288 + i * 32 + lane];
        s0 = fmaf(bf_lo(gv), bf_lo(a), fmaf(bf_hi(gv), bf_hi(a), s0));
        s1 = fmaf(bf_lo(gv), bf_lo(b), fmaf(bf_hi(gv), bf_hi(b), s1));
    }
#pragma unroll
    for (int o = 16; o; o >>= 1) { s0 += __shfl_xor_sync(~0u, s0, o); s1 += __shfl_xor_sync(~0u, s1, o); }
    g0 = 1.f / (1.f + __expf(-s0));
    g1 = 1.f / (1.f + __expf(-s1));
}

struct Maps { CUtensorMap m[6]; };

__global__ void __cluster_dims__(2, 1, 1) __launch_bounds__(NTHR, 1)
fused_kernel(const char* __restrict__ wq, const __nv_bfloat16* __restrict__ x, const __nv_bfloat16* __restrict__ b1,
             const __nv_bfloat16* __restrict__ b2, const __nv_bfloat16* __restrict__ gate_w,
             __nv_bfloat16* __restrict__ out, Scratch* __restrict__ scr, const __grid_constant__ Maps maps) {
    extern __shared__ __align__(1024) unsigned char smem_raw[];
    __shared__ Smem sm;
    asm volatile("{\n.reg .pred p;\n.reg .b32 t;\n.reg .b64 a;\nmov.u32 t, %%ctaid.x;\nmad.wide.u32 a, t, 36864, %0;\n"
                 "mov.u32 t, %%tid.x;\nsetp.eq.u32 p, t, 0;\n@p cp.async.bulk.prefetch.L2.global [a], 36864;\n}" ::"l"(wq) : "memory");
    const uint32_t ring = (s2u(smem_raw) + 1023u) & ~1023u;
    const int tid = threadIdx.x, lane = tid & 31;
    const int c = blockIdx.x;
    const int warp = __shfl_sync(~0u, tid >> 5, 0);

    if (tid == 0) {
#pragma unroll
        for (int i = 0; i < 6; i++) asm volatile("prefetch.tensormap [%0];" ::"l"(&maps.m[i]) : "memory");
#pragma unroll
        for (int i = 0; i < NST + NTAIL; i++) mbar_init(s2u(&sm.full[i]), 1);
#pragma unroll
        for (int i = 0; i < NST; i++) mbar_init(s2u(&sm.empty[i]), 4);
        mbar_init(s2u(&sm.obar), 128);
        asm volatile("fence.proxy.async.shared::cta;" ::: "memory");
    }
    if (tid < NITEM) {
        const int i = tid;
        const bool q = i < I_KV, kv = !q && i < I_W1, w1 = i >= I_W1 && i < I_W2, wo = i >= I_WO, w2o = i >= I_W2;
        const int k = i - (q ? 0 : kv ? I_KV : w1 ? I_W1 : wo ? I_WO : I_W2);
        const int kvrow = ((((c >> 2) & 1) * 16 + (c >> 3)) * SK) + (SK - WIN) + (c & 3) * 64;
        const uint32_t c0 = q ? c * 32 : w1 ? (c >> 1) * 72 : 0, c2 = w2o ? (c & 1) * 9 : 0;
        const uint32_t c1 = kv ? kvrow + (k >> 1) * 256 : k * (q ? 192 : w1 ? 96 : wo ? 16 : 24) + (q ? 0 : w1 ? (c & 1) * 288 : (c >> 1) * (wo ? 64 : 72));
        const uint32_t bytes = kv ? 16384 : q ? 12288 : wo ? 9216 : 13824;
        const uint32_t map = q ? 0 : kv ? 1 + (k & 1) : w1 ? 3 : wo ? 5 : 4;
        const int j = i - INFL;
        const int lap = (i >= NST) + (i >= 2 * NST) + (i >= 3 * NST), slot = i - lap * NST;
        const int jl = (j >= NST) + (j >= 2 * NST), js = j < 0 ? NST - 1 : j < I_W1 ? j - jl * NST : NST + j - I_W1;
        const uint32_t fl = (j < 0 ? 1 : j < I_W1 ? jl & 1 : 0) | ((~lap & 1) << 1) | (map << 10);
        const uint32_t bars = s2u(sm.full);
        sm.tab[i][0] = make_uint4(ring + slot * SLOT, bars + (i < I_W1 ? slot : NST + i - I_W1) * 8, c0, c1);
        sm.tab[i][1] = make_uint4(c2, bytes, bars + js * 8, fl | ((bars + (NST + NTAIL + slot) * 8) << 16));
    }
    int warp2;
    asm volatile("mov.u32 %0, %1;" : "=r"(warp2) : "r"(warp));
    if (warp2 == 0) {
        asm volatile("bar.arrive 0, %0;" ::"n"(NTHR) : "memory");
        __syncwarp();
        if (lane != 0) return;
        {
            uint64_t pol;
            asm volatile("createpolicy.fractional.L2::evict_first.b64 %0, 1.0;" : "=l"(pol));
#pragma unroll 1
            for (int i = 0; i < NITEM; i++) {
                const uint4 a = sm.tab[i][0], b = sm.tab[i][1];
                const char* map = reinterpret_cast<const char*>(&maps) + ((b.w >> 3) & 0x380);
                asm volatile("" : "+l"(map));
                mbar_wait((b.w >> 16) | (a.y & 0xff000000u), (b.w >> 1) & 1);
                mbar_expect(a.y, b.y);
                mbar_wait(b.z, b.w & 1);
                tma3d_ef(a.x, reinterpret_cast<const CUtensorMap*>(map), a.z, a.w, b.x, a.y, pol);
            }
        }
    }
    if (warp == 0) return;

    uint32_t bias_raw = 0;
    const int t = tid - (warp > 4 ? 160 : 32), w = warp - (warp > 4 ? 5 : 1);
    {
        const int l = tid - 32;
        const void* src = l < 144 ? (const void*)(x + l * 8) : l < 216 ? (const void*)(gate_w + (l - 144) * 8) : (const void*)&scr->ready;
        if (l <= 216) {
            uint4 v;
            asm volatile("ld.relaxed.gpu.global.v4.u32 {%0,%1,%2,%3}, [%4];" : "=r"(v.x), "=r"(v.y), "=r"(v.z), "=r"(v.w) : "l"(src));
            reinterpret_cast<uint4*>(sm.xs)[l] = v;
        }
    }
    if (warp > 4) bias_raw = ldg16(b1 + (c >> 1) * 72 + t % 72);
    if (tid == NTHR - 1) {
        mbar_init(s2u(&sm.hbar), 1);
        mbar_expect(s2u(&sm.hbar), 144 * 4);
    }
    bar_sync(0, NTHR);
    const uint32_t epoch = sm.ep[0] / NCTA;

    const uint32_t tag = (epoch + 1u) & 3u;
    const int rowl = ((lane >> 4) << 3) + (lane & 7);
    const int chl = (lane >> 3) & 1;
    const float SC = 0.08838834764831845f * 1.4426950408889634f;
    const int r4 = lane >> 2, jq = lane & 3;
    float g0, g1;
    int npass;
    asm volatile("mov.u32 %0, 2;" : "=r"(npass));

    if (warp > 4) {
        const uint32_t* xp = sm.xs + (r4 & 1) * 288 + jq;
        {
            float acc[2][4] = {};
            uint32_t xf[12];
#pragma unroll
            for (int j = 0; j < 12; j++) xf[j] = xp[(j >> 2) * 96 + w * 16 + (j & 3) * 4];
#pragma unroll
            for (int j = 0; j < 3; j++) {
                wait_full(sm, j);
#pragma unroll
                for (int i = 0; i < 2; i++) {
                    const int r = (w * 2 + i) * 16 + rowl;
#pragma unroll
                    for (int mt = 0; mt < 2; mt++) {
                        uint32_t a[4];
                        ldsm4t(a, ring + j * SLOT + r * 64 + (((mt * 2 + chl) ^ ((r >> 1) & 3)) << 4));
                        mma(acc[mt], a[0], a[1], a[2], a[3], xf[j * 4 + i * 2], xf[j * 4 + i * 2 + 1]);
                    }
                }
            }
            if (jq == 0) {
#pragma unroll
                for (int mt = 0; mt < 2; mt++) {
                    sm.red[w][0][mt * 16 + r4] = acc[mt][0];
                    sm.red[w][1][mt * 16 + r4] = acc[mt][1];
                    sm.red[w][0][mt * 16 + r4 + 8] = acc[mt][2];
                    sm.red[w][1][mt * 16 + r4 + 8] = acc[mt][3];
                }
            }
            bar_sync(1, 192);
            if (t < 32) {
                const int bq = t >> 4, p = t & 15;
                float q0 = 0.f, q1 = 0.f;
#pragma unroll
                for (int k = 0; k < 6; k++) { const float2 v = *reinterpret_cast<const float2*>(&sm.red[k][bq][p * 2]); q0 += v.x; q1 += v.y; }
                st_msg2(&scr->q[bq * 4096 + c * 32 + p * 2], q0, q1, tag);
            } else if (t < 44) {
                release(sm, (t >> 2) - 8);
            }
            bar_sync(1, 192);
        }
        if (t < 72) st_zero4(scr->o + (size_t)c * 288 + t * 4);
        gate(sm, lane, g0, g1);
        float* ap = scr->acc + (((c & 1) * 192 + t) >> 1) * ACC_PITCH + (t & 1) * 4;
        const int e0 = (c & 1) * 288 + w * 48 + jq * 8 + r4, e2 = (c & 1) * 288 + w * 48 + 32 + (jq & 1) * 8 + r4;
        if (c < 2) {
            const float ba = bf_lo(ldg16(b2 + e0)), bb = bf_lo(ldg16(b2 + e2));
            asm volatile("st.relaxed.gpu.global.v4.f32 [%0], {%1,%2,%3,%4};"
                         ::"l"(ap), "f"((1.f - g0) * ba), "f"((1.f - g1) * ba), "f"((1.f - ((jq & 2) ? g1 : g0)) * bb), "f"(0.f) : "memory");
        }
        uint32_t xf[6];
#pragma unroll
        for (int j = 0; j < 6; j++) xf[j] = xp[(c & 1) * 144 + (j >> 1) * 48 + w * 8 + (j & 1) * 4];
#pragma unroll 1
        for (int pass = 0; pass < npass; pass++) {
            {
                float acc[5][4] = {};
#pragma unroll
                for (int j = 0; j < 3; j++) {
                    if (pass) wait_full(sm, I_W1 + j);
                    const uint32_t base = ring + ((I_W1 + j) % NST) * SLOT + (w * 16 + rowl) * 144 + chl * 16;
#pragma unroll
                    for (int mt = 0; mt < 5; mt++) {
                        uint32_t a[4];
                        ldsm4t(a, base + mt * 32);
                        mma(acc[mt], a[0], a[1], a[2], a[3], xf[j * 2], xf[j * 2 + 1]);
                    }
                }
                if (jq == 0) {
#pragma unroll
                    for (int mt = 0; mt < 5; mt++) {
                        sm.red[w][0][mt * 16 + r4] = acc[mt][0];
                        sm.red[w][1][mt * 16 + r4] = acc[mt][1];
                        if (mt < 4) {
                            sm.red[w][0][mt * 16 + r4 + 8] = acc[mt][2];
                            sm.red[w][1][mt * 16 + r4 + 8] = acc[mt][3];
                        }
                    }
                }
                bar_sync(1, 192);
                if (t < 144) {
                    const int bb = t >= 72, k = t - bb * 72;
                    float h = 0.f;
#pragma unroll
                    for (int i = 0; i < 6; i++) h += sm.red[i][bb][k];
                    if (pass) {
                        asm volatile("{\n.reg .b32 a, b;\nmapa.shared::cluster.u32 a, %0, %3;\nmapa.shared::cluster.u32 b, %2, %3;\n"
                                     "st.async.shared::cluster.mbarrier::complete_tx::bytes.f32 [a], %1, [b];\n}"
                                     ::"r"(s2u(&sm.hx[t])), "f"(h), "r"(s2u(&sm.hbar)), "r"(~c & 1) : "memory");
                        uint32_t ok;
                        int it = 0;
                        do {
                            asm volatile("{\n.reg .pred p;\nmbarrier.try_wait.parity.acquire.cluster.shared::cta.b64 p, [%1], 0;\nselp.u32 %0, 1, 0, p;\n}"
                                         : "=r"(ok) : "r"(s2u(&sm.hbar)) : "memory");
                        } while (!ok && ++it < SPIN_LIMIT);
                    }
                    h = bf_round(h + sm.hx[t]);
                    h = fmaxf(bf_round(h + bf_lo(bias_raw)), 0.f);
                    reinterpret_cast<__nv_bfloat16*>(sm.hs)[t] = __float2bfloat16_rn(h * h);
                }
                bar_sync(1, 192);
            }
            float acc[3][4] = {};
            {
                uint32_t hb[9];
#pragma unroll
                for (int k = 0; k < 9; k++) hb[k] = sm.hs[r4 & 1][k * 4 + jq];
#pragma unroll
                for (int j = 0; j < 3; j++) {
                    if (pass) wait_full(sm, I_W2 + j);
#pragma unroll
                    for (int i = 0; i < 3; i++) {
                        const int mt = w * 3 + i;
#pragma unroll
                        for (int ks = 0; ks < 2; ks++) {
                            const int r = ks ? 16 + (lane & 7) : rowl;
                            uint32_t a[4];
                            ldsm4t(a, ring + ((I_W2 + j) % NST) * SLOT + (mt >> 1) * 1536 + r * 64 + ((((mt & 1) * 2 + chl) ^ ((r >> 1) & 3)) << 4));
                            mma(acc[i], a[0], a[1], a[2], a[3], hb[j * 3 + ks * 2], ks ? 0u : hb[j * 3 + 1]);
                        }
                    }
                }
#pragma unroll
                for (int i = 0; i < 3; i++) { acc[i][0] *= 1.f - g0; acc[i][1] *= 1.f - g1; acc[i][2] *= 1.f - g0; acc[i][3] *= 1.f - g1; }
            }
            if (pass) mbar_wait(s2u(&sm.obar), 0);
            uint32_t ob[8];
#pragma unroll
            for (int k = 0; k < 8; k++) ob[k] = sm.os[r4 & 1][k * 4 + jq];
#pragma unroll
            for (int j = 0; j < 4; j++) {
                if (pass) wait_full(sm, I_WO + j);
#pragma unroll
                for (int i = 0; i < 3; i++) {
                    const int mt = w * 3 + i;
                    uint32_t a[4];
                    ldsm4t(a, ring + ((I_WO + j) % NST) * SLOT + (mt >> 1) * 1024 + rowl * 64 + ((((mt & 1) * 2 + chl) ^ ((rowl >> 1) & 3)) << 4));
                    mma(acc[i], a[0], a[1], a[2], a[3], ob[j * 2], ob[j * 2 + 1]);
                }
            }
            {
                const float u0 = (jq & 1) ? acc[0][2] : acc[0][0], u1 = (jq & 1) ? acc[0][3] : acc[0][1];
                const float v0 = (jq & 1) ? acc[1][2] : acc[1][0], v1 = (jq & 1) ? acc[1][3] : acc[1][1];
                const float p0 = (jq & 2) ? v0 : u0, p1 = (jq & 2) ? v1 : u1;
                const float p2 = (jq & 1) ? ((jq & 2) ? acc[2][3] : acc[2][2]) : ((jq & 2) ? acc[2][1] : acc[2][0]);
                float s0 = 0.f, s1 = 0.f, s2 = 0.f, n = 0.f;
                asm volatile("{\n.reg .pred p;\nsetp.ne.u32 p, %9, 0;\n@p atom.relaxed.gpu.global.add.v4.f32 {%0,%1,%2,%3}, [%4], {%5,%6,%7,%8};\n}"
                             : "+f"(s0), "+f"(s1), "+f"(s2), "+f"(n) : "l"(ap), "f"(p0), "f"(p1), "f"(p2), "f"(1.f), "r"(pass) : "memory");
                if (n == (float)(NCTA / 2 - 1)) {
                    out[e0] = __float2bfloat16_rn(s0 + p0);
                    out[e0 + D_MODEL] = __float2bfloat16_rn(s1 + p1);
                    out[e2 + (jq >> 1) * D_MODEL] = __float2bfloat16_rn(s2 + p2);
                }
            }
            if (!pass) {
                bar_sync(1, 192);
                if (t == 0) asm volatile("red.release.gpu.global.add.u32 [%0], 1;" ::"l"(&scr->ready) : "memory");
            }
        }
        return;
    }

    gate(sm, lane, g0, g1);
#pragma unroll 1
    for (int pass = 0; pass < npass; pass++) {
        float o[8][4] = {};
        float m = -INFINITY, l = 0.f;
        if (pass) {
            const float* qp = scr->q + ((c >> 2) & 1) * 4096 + (c >> 3) * 256 + t * 2;
            uint2 v;
            int it = 0;
            wait_full(sm, I_QPOLL);
            do { v = ld_msg2(qp); } while (!ok2(v, tag) && ++it < SPIN_LIMIT);
            (&sm.qs[0][0])[t] = pack_bf16(__uint_as_float(v.x), __uint_as_float(v.y));
            bar_sync(3, 128);
            uint32_t qf[16];
#pragma unroll
            for (int ks = 0; ks < 8; ks++) {
                qf[2 * ks] = lane < 8 ? sm.qs[lane >> 2][ks * 8 + (lane & 3)] : 0u;
                qf[2 * ks + 1] = lane < 8 ? sm.qs[lane >> 2][ks * 8 + 4 + (lane & 3)] : 0u;
            }
            const int key = w * 16 + rowl;
            const uint32_t off = key * 128;
            const int sw = key & 7;
#pragma unroll 1
            for (int tl = 0; tl < 16; tl++) {
                const int ik = I_KV + 2 * tl, iv = ik + 1;
                if (tl == RDY_TL && t == 0) {
                    uint32_t seen;
                    it = 0;
                    do {
                        asm volatile("ld.acquire.gpu.global.u32 %0, [%1];" : "=r"(seen) : "l"(&scr->ready) : "memory");
                    } while ((int)(seen - (epoch + 1u) * NCTA) < 0 && ++it < SPIN_LIMIT);
                }
                wait_full(sm, ik);
                const uint32_t kb = ring + (ik % NST) * SLOT + off;
                float s[2][2][4] = {};
#pragma unroll
                for (int ks = 0; ks < 8; ks++) {
                    uint32_t kf[4];
                    ldsm4(kf, kb + (ks >> 2) * 8192 + ((((ks & 3) * 2 + chl) ^ sw) << 4));
                    mma(s[0][ks & 1], qf[2 * ks], 0u, qf[2 * ks + 1], 0u, kf[0], kf[1]);
                    mma(s[1][ks & 1], qf[2 * ks], 0u, qf[2 * ks + 1], 0u, kf[2], kf[3]);
                }
                __syncwarp();
                if (lane == 0) release(sm, ik);
                const float s0 = s[0][0][0] + s[0][1][0], s1 = s[0][0][1] + s[0][1][1];
                const float s2 = s[1][0][0] + s[1][1][0], s3 = s[1][0][1] + s[1][1][1];
                float mx = fmaxf(fmaxf(s0, s1), fmaxf(s2, s3));
                mx = fmaxf(mx, __shfl_xor_sync(~0u, mx, 1));
                mx = fmaxf(mx, __shfl_xor_sync(~0u, mx, 2));
                const float mn = fmaxf(m, mx);
                const float al = ex2((m - mn) * SC);
                m = mn;
                const float ms = mn * SC;
                const uint32_t p0 = pack_bf16(ex2(fmaf(s0, SC, -ms)), ex2(fmaf(s1, SC, -ms)));
                const uint32_t p1 = pack_bf16(ex2(fmaf(s2, SC, -ms)), ex2(fmaf(s3, SC, -ms)));
                l = fmaf(l, al, (bf_lo(p0) + bf_hi(p0)) + (bf_lo(p1) + bf_hi(p1)));
                const float a0 = __shfl_sync(~0u, al, 0), a1 = __shfl_sync(~0u, al, 4);
                if (a0 != 1.f || a1 != 1.f) {
#pragma unroll
                    for (int mt = 0; mt < 8; mt++) { o[mt][0] *= a0; o[mt][1] *= a1; o[mt][2] *= a0; o[mt][3] *= a1; }
                }
                wait_full(sm, iv);
                const uint32_t vb = ring + (iv % NST) * SLOT + off;
#pragma unroll
                for (int mt = 0; mt < 8; mt++) {
                    uint32_t vf[4];
                    ldsm4t(vf, vb + (mt >> 2) * 8192 + ((((mt & 3) * 2 + chl) ^ sw) << 4));
                    mma(o[mt], vf[0], vf[1], vf[2], vf[3], p0, p1);
                }
                __syncwarp();
                if (lane == 0) release(sm, iv);
            }
        }
        l += __shfl_xor_sync(~0u, l, 1);
        l += __shfl_xor_sync(~0u, l, 2);
        if (lane == 0 || lane == 4) { sm.ml[w][lane >> 2][0] = m; sm.ml[w][lane >> 2][1] = l; }
        if ((lane & 3) == 0) {
#pragma unroll
            for (int mt = 0; mt < 8; mt++) {
                sm.ocomb[w][0][mt * 16 + r4] = o[mt][0];
                sm.ocomb[w][1][mt * 16 + r4] = o[mt][1];
                sm.ocomb[w][0][mt * 16 + r4 + 8] = o[mt][2];
                sm.ocomb[w][1][mt * 16 + r4 + 8] = o[mt][3];
            }
        }
        bar_sync(3, 128);
        {
            const int h = t >> 6, d = (t & 63) * 2;
            const float M = fmaxf(fmaxf(sm.ml[0][h][0], sm.ml[1][h][0]), fmaxf(sm.ml[2][h][0], sm.ml[3][h][0]));
            float L = 0.f, O0 = 0.f, O1 = 0.f;
#pragma unroll
            for (int k = 0; k < 4; k++) {
                const float sc = ex2((sm.ml[k][h][0] - M) * SC);
                const float2 ov = *reinterpret_cast<const float2*>(&sm.ocomb[k][h][d]);
                L = fmaf(sc, sm.ml[k][h][1], L);
                O0 = fmaf(sc, ov.x, O0);
                O1 = fmaf(sc, ov.y, O1);
            }
            float* dst = scr->o + ((size_t)((c >> 3) * 4 + w) * 8 + (c & 7)) * 72;
            st_val2_if(dst + lane * 2, O0, O1, pass);
            st_val2_if(dst + 64 + lane * 2, M, L, pass && lane < 4);
        }
        {
            const int bb = t >> 6, col = t & 60;
            const float* src = scr->o + ((size_t)(c >> 1) * 8 + bb * 4 + jq) * 72;
            uint4 v = make_uint4(!pass, 1u, 1u, 1u);
            uint2 ml = make_uint2(!pass, 1u);
            int it = 0;
            do {
                ld_msg4_if(v, src + col, !val4(v));
                ld_msg2_if(ml, src + 64, !val2(ml));
            } while (!(val4(v) && val2(ml)) && ++it < SPIN_LIMIT);
            __syncwarp();
            const float mm = __uint_as_float(ml.x);
            float M = fmaxf(mm, __shfl_xor_sync(~0u, mm, 1));
            M = fmaxf(M, __shfl_xor_sync(~0u, M, 2));
            const float f = ex2((mm - M) * SC);
            float L = f * __uint_as_float(ml.y);
            const bool hi = jq & 1;
            float o0 = f * __uint_as_float(hi ? v.z : v.x), o1 = f * __uint_as_float(hi ? v.w : v.y);
            o0 += __shfl_xor_sync(~0u, f * __uint_as_float(hi ? v.x : v.z), 1);
            o1 += __shfl_xor_sync(~0u, f * __uint_as_float(hi ? v.y : v.w), 1);
            L += __shfl_xor_sync(~0u, L, 1);
            o0 += __shfl_xor_sync(~0u, o0, 2);
            o1 += __shfl_xor_sync(~0u, o1, 2);
            L += __shfl_xor_sync(~0u, L, 2);
            const float inv = (bb ? g1 : g0) * rcp(L);
            if (pass) {
                if (jq < 2) sm.os[bb][(col >> 1) + jq] = pack_bf16(o0 * inv, o1 * inv);
                mbar_arrive(s2u(&sm.obar));
            }
        }
    }
}

typedef CUresult (*EncFn)(CUtensorMap*, CUtensorMapDataType, cuuint32_t, void*, const cuuint64_t*, const cuuint64_t*,
                          const cuuint32_t*, const cuuint32_t*, CUtensorMapInterleave, CUtensorMapSwizzle,
                          CUtensorMapL2promotion, CUtensorMapFloatOOBfill);

}

extern "C" void kernel_launch(void* const* d_in, const int* in_sizes, int n_in, void* d_out, int out_size) {
    (void)in_sizes; (void)n_in; (void)out_size;
    EncFn enc = nullptr;
    cudaDriverEntryPointQueryResult qr;
    cudaGetDriverEntryPoint("cuTensorMapEncodeTiled", (void**)&enc, cudaEnableDefault, &qr);
    Maps maps;
    const CUtensorMapL2promotion pr = CU_TENSOR_MAP_L2_PROMOTION_L2_256B;
    auto mk = [&](int i, void* p, uint64_t d0, uint64_t d1, uint64_t d2, uint64_t s1, uint64_t s2, uint32_t b0, uint32_t b1, uint32_t b2,
                  CUtensorMapSwizzle sw) {
        cuuint64_t d[3] = {d0, d1, d2}, s[2] = {s1, s2};
        cuuint32_t b[3] = {b0, b1, b2}, e[3] = {1, 1, 1};
        enc(&maps.m[i], CU_TENSOR_MAP_DATA_TYPE_BFLOAT16, 3, p, d, s, b, e, CU_TENSOR_MAP_INTERLEAVE_NONE, sw, pr,
            CU_TENSOR_MAP_FLOAT_OOB_FILL_NONE);
    };
    mk(0, d_in[3], 4096, 576, 1, 8192, 8192 * 576, 32, 192, 1, CU_TENSOR_MAP_SWIZZLE_64B);
    mk(1, d_in[1], 64, 32ull * SK, 2, 256, 128, 64, 64, 2, CU_TENSOR_MAP_SWIZZLE_128B);
    mk(2, d_in[2], 64, 32ull * SK, 2, 256, 128, 64, 64, 2, CU_TENSOR_MAP_SWIZZLE_128B);
    mk(3, d_in[6], 4608, 576, 1, 9216, 9216 * 576, 72, 96, 1, CU_TENSOR_MAP_SWIZZLE_NONE);
    mk(4, d_in[8], 32, 4608, 18, 1152, 64, 32, 24, 9, CU_TENSOR_MAP_SWIZZLE_64B);
    mk(5, d_in[4], 32, 4096, 18, 1152, 64, 32, 16, 9, CU_TENSOR_MAP_SWIZZLE_64B);
    const int smem = NST * SLOT + 1024;
    cudaFuncSetAttribute(fused_kernel, cudaFuncAttributeMaxDynamicSharedMemorySize, smem);
    void* scr = nullptr;
    cudaGetSymbolAddress(&scr, g_scr);
    fused_kernel<<<NCTA, NTHR, smem, cudaStreamPerThread>>>(
        (const char*)d_in[3], (const __nv_bfloat16*)d_in[0], (const __nv_bfloat16*)d_in[7], (const __nv_bfloat16*)d_in[9],
        (const __nv_bfloat16*)d_in[10], (__nv_bfloat16*)d_out, (Scratch*)scr, maps);
}
```

```cpp
#include <cuda_runtime.h>
#include <cuda_bf16.h>
#include <cuda.h>
#include <stdint.h>

namespace {

constexpr int D_MODEL = 576;
constexpr int SK = 32768;
constexpr int WIN = 4096;
constexpr int NCTA = 128;
constexpr int SLOT = 16384;
constexpr int NST = 12;
constexpr int INFL = 4;
constexpr int LO = 2, HI = 5;
constexpr int PACE = 20971;
constexpr int LEAD = 1400;
constexpr int I_K = 3, I_V = 19, I_W1 = 35, I_W2 = 38, I_WO = 41, NITEM = 45;
constexpr int NTAIL = NITEM - I_W1;
constexpr int NTHR = 352;
constexpr int I_QPOLL = 5;
constexpr int I_OPOLL = 36;
constexpr int ACC_PITCH = 32;
constexpr int SPIN_LIMIT = 1 << 17;

struct Scratch {
    float acc[192 * ACC_PITCH];
    float o[NCTA / 2 * 8 * 72];
    float q[2 * 4096];
    unsigned ready, pad[3];
};
__device__ __align__(128) Scratch g_scr;

struct __align__(16) Smem {
    uint4 tab[NITEM][2];
    uint2 tab2[NITEM + 1];
    uint64_t full[NST + NTAIL];
    uint64_t empty[NST];
    uint64_t obar, hbar;
    uint32_t xs[2 * 288];
    uint32_t gw[288];
    uint32_t ep[4];
    float red[6][2][80];
    float hx[144];
    float ocomb[4][2][128];
    float ml[4][2][2];
    float4 sc[4][16][8];
    uint32_t qs[2][64];
    uint32_t hs[2][36];
    uint32_t os[2][36];
};

__device__ __forceinline__ uint32_t s2u(const void* p) { return (uint32_t)__cvta_generic_to_shared(p); }
__device__ __forceinline__ void mbar_init(uint32_t a, int c) { asm volatile("mbarrier.init.shared.b64 [%0], %1;" ::"r"(a), "r"(c) : "memory"); }
__device__ __forceinline__ void mbar_expect(uint32_t a, uint32_t b) { asm volatile("mbarrier.arrive.expect_tx.shared.b64 _, [%0], %1;" ::"r"(a), "r"(b) : "memory"); }
__device__ __forceinline__ void mbar_arrive(uint32_t a) { asm volatile("mbarrier.arrive.shared.b64 _, [%0];" ::"r"(a) : "memory"); }
__device__ __forceinline__ void mbar_wait(uint32_t a, uint32_t ph) {
    uint32_t ok;
    int it = 0;
    do {
        asm volatile("{\n.reg .pred p;\nmbarrier.try_wait.parity.shared.b64 p, [%1], %2;\nselp.u32 %0, 1, 0, p;\n}" : "=r"(ok) : "r"(a), "r"(ph) : "memory");
    } while (!ok && ++it < SPIN_LIMIT);
}
__device__ __forceinline__ void tma3d_ef(uint32_t dst, const CUtensorMap* m, int c0, int c1, int c2, uint32_t bar, uint64_t pol) {
    asm volatile("cp.async.bulk.tensor.3d.shared::cluster.global.mbarrier::complete_tx::bytes.L2::cache_hint [%0], [%1, {%3, %4, %5}], [%2], %6;"
                 ::"r"(dst), "l"(m), "r"(bar), "r"(c0), "r"(c1), "r"(c2), "l"(pol) : "memory");
}
__device__ __forceinline__ void ldsm4(uint32_t* r, uint32_t a) {
    asm volatile("ldmatrix.sync.aligned.m8n8.x4.shared.b16 {%0,%1,%2,%3}, [%4];" : "=r"(r[0]), "=r"(r[1]), "=r"(r[2]), "=r"(r[3]) : "r"(a) : "memory");
}
__device__ __forceinline__ void ldsm4t(uint32_t* r, uint32_t a) {
    asm volatile("ldmatrix.sync.aligned.m8n8.x4.trans.shared.b16 {%0,%1,%2,%3}, [%4];" : "=r"(r[0]), "=r"(r[1]), "=r"(r[2]), "=r"(r[3]) : "r"(a) : "memory");
}
__device__ __forceinline__ void mma(float* c, uint32_t a0, uint32_t a1, uint32_t a2, uint32_t a3, uint32_t b0, uint32_t b1) {
    asm volatile("mma.sync.aligned.m16n8k16.row.col.f32.bf16.bf16.f32 {%0,%1,%2,%3}, {%4,%5,%6,%7}, {%8,%9}, {%0,%1,%2,%3};"
                 : "+f"(c[0]), "+f"(c[1]), "+f"(c[2]), "+f"(c[3]) : "r"(a0), "r"(a1), "r"(a2), "r"(a3), "r"(b0), "r"(b1));
}
__device__ __forceinline__ uint32_t pack_bf16(float lo, float hi) {
    uint32_t r;
    asm("cvt.rn.bf16x2.f32 %0, %1, %2;" : "=r"(r) : "f"(hi), "f"(lo));
    return r;
}
__device__ __forceinline__ float bf_lo(uint32_t v) { return __uint_as_float(v << 16); }
__device__ __forceinline__ float bf_hi(uint32_t v) { return __uint_as_float(v & 0xffff0000u); }
__device__ __forceinline__ float bf_round(float v) { return __bfloat162float(__float2bfloat16_rn(v)); }
__device__ __forceinline__ float ex2(float v) { float r; asm("ex2.approx.ftz.f32 %0, %1;" : "=f"(r) : "f"(v)); return r; }
__device__ __forceinline__ float rcp(float v) { float r; asm("rcp.approx.ftz.f32 %0, %1;" : "=f"(r) : "f"(v)); return r; }
__device__ __forceinline__ uint32_t ldg16(const void* p) {
    uint32_t v;
    asm volatile("ld.global.nc.u16 %0, [%1];" : "=r"(v) : "l"(p));
    return v;
}
__device__ __forceinline__ uint32_t tagw(float v, uint32_t tag) { return (__float_as_uint(v) & ~3u) | tag; }
__device__ __forceinline__ void st_msg2(float* p, float a, float b, uint32_t tag) {
    asm volatile("st.relaxed.gpu.global.v2.u32 [%0], {%1,%2};" ::"l"(p), "r"(tagw(a, tag)), "r"(tagw(b, tag)) : "memory");
}
__device__ __forceinline__ void st_zero4(float* p) {
    asm volatile("st.relaxed.gpu.global.v4.u32 [%0], {%1,%1,%1,%1};" ::"l"(p), "r"(0u) : "memory");
}
__device__ __forceinline__ void st_val2_if(float* p, float a, float b, uint32_t pred) {
    asm volatile("{\n.reg .pred p;\nsetp.ne.u32 p, %3, 0;\n@p st.relaxed.gpu.global.v2.u32 [%0], {%1,%2};\n}"
                 ::"l"(p), "r"(__float_as_uint(a) | 1u), "r"(__float_as_uint(b) | 1u), "r"(pred) : "memory");
}
__device__ __forceinline__ uint2 ld_msg2(const float* p) {
    uint2 v;
    asm volatile("ld.relaxed.gpu.global.v2.u32 {%0,%1}, [%2];" : "=r"(v.x), "=r"(v.y) : "l"(p) : "memory");
    return v;
}
__device__ __forceinline__ void ld_msg2_if(uint2& v, const float* p, bool pred) {
    asm volatile("{\n.reg .pred p;\nsetp.ne.u32 p, %3, 0;\n@p ld.relaxed.gpu.global.v2.u32 {%0,%1}, [%2];\n}"
                 : "+r"(v.x), "+r"(v.y) : "l"(p), "r"((uint32_t)pred) : "memory");
}
__device__ __forceinline__ void ld_msg4_if(uint4& v, const float* p, bool pred) {
    asm volatile("{\n.reg .pred p;\nsetp.ne.u32 p, %5, 0;\n@p ld.relaxed.gpu.global.v4.u32 {%0,%1,%2,%3}, [%4];\n}"
                 : "+r"(v.x), "+r"(v.y), "+r"(v.z), "+r"(v.w) : "l"(p), "r"((uint32_t)pred) : "memory");
}
__device__ __forceinline__ bool val4(uint4 v) { return v.x & v.y & v.z & v.w & 1u; }
__device__ __forceinline__ bool ok2(uint2 v, uint32_t tag) { return (((v.x ^ tag) | (v.y ^ tag)) & 3u) == 0; }
__device__ __forceinline__ bool val2(uint2 v) { return v.x & v.y & 1u; }
__device__ __forceinline__ void bar_sync(int id, int n) { asm volatile("bar.sync %0, %1;" ::"r"(id), "r"(n) : "memory"); }
__device__ __forceinline__ uint32_t full_bar(Smem& sm, int i) { return s2u(&sm.full[i < I_W1 ? i % NST : NST + i - I_W1]); }
__device__ __forceinline__ void wait_full(Smem& sm, int i) { mbar_wait(full_bar(sm, i), i < I_W1 ? (i / NST) & 1 : 0); }
__device__ __forceinline__ void release(Smem& sm, int i) { mbar_arrive(s2u(&sm.empty[i % NST])); }

__device__ __forceinline__ void gate(const Smem& sm, int lane, float& g0, float& g1) {
    float s0 = 0.f, s1 = 0.f;
#pragma unroll
    for (int i = 0; i < 9; i++) {
        const uint32_t gv = sm.gw[i * 32 + lane], a = sm.xs[i * 32 + lane], b = sm.xs[288 + i * 32 + lane];
        s0 = fmaf(bf_lo(gv), bf_lo(a), fmaf(bf_hi(gv), bf_hi(a), s0));
        s1 = fmaf(bf_lo(gv), bf_lo(b), fmaf(bf_hi(gv), bf_hi(b), s1));
    }
#pragma unroll
    for (int o = 16; o; o >>= 1) { s0 += __shfl_xor_sync(~0u, s0, o); s1 += __shfl_xor_sync(~0u, s1, o); }
    g0 = 1.f / (1.f + __expf(-s0));
    g1 = 1.f / (1.f + __expf(-s1));
}

struct Maps { CUtensorMap m[6]; };

__global__ void __cluster_dims__(2, 1, 1) __launch_bounds__(NTHR, 1)
fused_kernel(const char* __restrict__ wq, const __nv_bfloat16* __restrict__ x, const __nv_bfloat16* __restrict__ b1,
             const __nv_bfloat16* __restrict__ b2, const __nv_bfloat16* __restrict__ gate_w,
             __nv_bfloat16* __restrict__ out, Scratch* __restrict__ scr, const __grid_constant__ Maps maps) {
    extern __shared__ __align__(1024) unsigned char smem_raw[];
    __shared__ Smem sm;
    asm volatile("{\n.reg .pred p;\n.reg .b32 t;\n.reg .b64 a;\nmov.u32 t, %%ctaid.x;\nmad.wide.u32 a, t, 36864, %0;\n"
                 "mov.u32 t, %%tid.x;\nsetp.eq.u32 p, t, 0;\n@p cp.async.bulk.prefetch.L2.global [a], 36864;\n}" ::"l"(wq) : "memory");
    const uint32_t ring = (s2u(smem_raw) + 1023u) & ~1023u;
    const int tid = threadIdx.x, lane = tid & 31;
    const int c = blockIdx.x;
    const int warp = __shfl_sync(~0u, tid >> 5, 0);

    if (tid == 0) {
#pragma unroll
        for (int i = 0; i < 6; i++) asm volatile("prefetch.tensormap [%0];" ::"l"(&maps.m[i]) : "memory");
#pragma unroll
        for (int i = 0; i < NST + NTAIL; i++) mbar_init(s2u(&sm.full[i]), 1);
#pragma unroll
        for (int i = 0; i < NST; i++) mbar_init(s2u(&sm.empty[i]), 4);
        mbar_init(s2u(&sm.obar), 128);
        asm volatile("fence.proxy.async.shared::cta;" ::: "memory");
    }
    if (tid < NITEM) {
        const int i = tid;
        const bool q = i < I_K, kv = !q && i < I_W1, w1 = i >= I_W1 && i < I_W2, wo = i >= I_WO, w2o = i >= I_W2;
        const int k = i - (q ? 0 : kv ? I_K : w1 ? I_W1 : wo ? I_WO : I_W2);
        const int kvrow = ((((c >> 2) & 1) * 16 + (c >> 3)) * SK) + (SK - WIN) + (c & 3) * 64;
        const uint32_t c0 = q ? c * 32 : w1 ? (c >> 1) * 72 : 0, c2 = w2o ? (c & 1) * 9 : 0;
        const uint32_t c1 = kv ? kvrow + (k & 15) * 256 : k * (q ? 192 : w1 ? 96 : wo ? 16 : 24) + (q ? 0 : w1 ? (c & 1) * 288 : (c >> 1) * (wo ? 64 : 72));
        const uint32_t bytes = kv ? 16384 : q ? 12288 : wo ? 9216 : 13824;
        const uint32_t map = q ? 0 : kv ? 1 + (k >> 4) : w1 ? 3 : wo ? 5 : 4;
        const int j = i - HI;
        const int j2 = i < INFL ? -1 : i - LO;
        const int jl2 = (j2 >= NST) + (j2 >= 2 * NST), js2 = j2 < 0 ? NST - 1 : j2 < I_W1 ? j2 - jl2 * NST : NST + j2 - I_W1;
        const int cum = (q ? 0 : kv ? 36864 : w1 ? 36864 + 32 * 16384 : wo ? 36864 + 32 * 16384 + 6 * 13824 : 36864 + 32 * 16384 + 3 * 13824) + (k + 1) * bytes;
        uint32_t now;
        asm volatile("mov.u32 %0, %%globaltimer_lo;" : "=r"(now));
        const int lap = (i >= NST) + (i >= 2 * NST) + (i >= 3 * NST), slot = i - lap * NST;
        const int jl = (j >= NST) + (j >= 2 * NST), js = j < 0 ? NST - 1 : j < I_W1 ? j - jl * NST : NST + j - I_W1;
        const uint32_t fl = (j < 0 ? 1 : j < I_W1 ? jl & 1 : 0) | ((~lap & 1) << 1) | ((j2 < 0 ? 1 : j2 < I_W1 ? jl2 & 1 : 0) << 2) | (map << 10);
        const uint32_t bars = s2u(sm.full);
        sm.tab[i][0] = make_uint4(ring + slot * SLOT, bars + (i < I_W1 ? slot : NST + i - I_W1) * 8, c0, c1);
        sm.tab[i][1] = make_uint4(c2, bytes, bars + js * 8, fl | ((bars + (NST + NTAIL + slot) * 8) << 16));
        sm.tab2[i] = make_uint2(bars + js2 * 8, now + (((cum >> 9) * PACE) >> 10) - LEAD);
    }
    int warp2;
    asm volatile("mov.u32 %0, %1;" : "=r"(warp2) : "r"(warp));
    if (warp2 == 0) {
        asm volatile("bar.arrive 0, %0;" ::"n"(NTHR) : "memory");
        __syncwarp();
        if (lane != 0) return;
        {
            uint64_t pol;
            asm volatile("createpolicy.fractional.L2::evict_first.b64 %0, 1.0;" : "=l"(pol));
#pragma unroll 1
            for (int i = 0; i < NITEM; i++) {
                const uint4 a = sm.tab[i][0], b = sm.tab[i][1];
                const char* map = reinterpret_cast<const char*>(&maps) + ((b.w >> 3) & 0x380);
                asm volatile("" : "+l"(map));
                mbar_wait((b.w >> 16) | (a.y & 0xff000000u), (b.w >> 1) & 1);
                mbar_expect(a.y, b.y);
                mbar_wait(b.z, b.w & 1);
                {
                    const uint2 d = sm.tab2[i];
                    uint32_t go;
                    int it = 0;
                    do {
                        asm volatile("{\n.reg .pred p;\n.reg .b32 t;\nmov.u32 t, %%globaltimer_lo;\nmbarrier.test_wait.parity.shared.b64 p, [%1], %2;\n"
                                     "sub.s32 t, t, %3;\nsetp.ge.or.s32 p, t, 0, p;\nselp.u32 %0, 1, 0, p;\n}"
                                     : "=r"(go) : "r"(d.x), "r"((b.w >> 2) & 1), "r"(d.y) : "memory");
                    } while (!go && ++it < SPIN_LIMIT);
                }
                tma3d_ef(a.x, reinterpret_cast<const CUtensorMap*>(map), a.z, a.w, b.x, a.y, pol);
            }
        }
    }
    if (warp == 0) return;

    uint32_t bias_raw = 0;
    const int t = tid - (warp > 4 ? 160 : 32), w = warp - (warp > 4 ? 5 : 1);
    {
        const int l = tid - 32;
        const void* src = l < 144 ? (const void*)(x + l * 8) : l < 216 ? (const void*)(gate_w + (l - 144) * 8) : (const void*)&scr->ready;
        if (l <= 216) {
            uint4 v;
            asm volatile("ld.relaxed.gpu.global.v4.u32 {%0,%1,%2,%3}, [%4];" : "=r"(v.x), "=r"(v.y), "=r"(v.z), "=r"(v.w) : "l"(src));
            reinterpret_cast<uint4*>(sm.xs)[l] = v;
        }
    }
    if (warp > 4) bias_raw = ldg16(b1 + (c >> 1) * 72 + t % 72);
    if (tid == 351) {
        mbar_init(s2u(&sm.hbar), 1);
        mbar_expect(s2u(&sm.hbar), 144 * 4);
    }
    bar_sync(0, NTHR);
    const uint32_t epoch = sm.ep[0] / NCTA;

    const uint32_t tag = (epoch + 1u) & 3u;
    const int rowl = ((lane >> 4) << 3) + (lane & 7);
    const int chl = (lane >> 3) & 1;
    const float SC = 0.08838834764831845f * 1.4426950408889634f;
    const int r4 = lane >> 2, jq = lane & 3;
    float g0, g1;
    int npass;
    asm volatile("mov.u32 %0, 2;" : "=r"(npass));

    if (warp > 4) {
        const uint32_t* xp = sm.xs + (r4 & 1) * 288 + jq;
        {
            float acc[2][4] = {};
            uint32_t xf[12];
#pragma unroll
            for (int j = 0; j < 12; j++) xf[j] = xp[(j >> 2) * 96 + w * 16 + (j & 3) * 4];
#pragma unroll
            for (int j = 0; j < 3; j++) {
                wait_full(sm, j);
#pragma unroll
                for (int i = 0; i < 2; i++) {
                    const int r = (w * 2 + i) * 16 + rowl;
#pragma unroll
                    for (int mt = 0; mt < 2; mt++) {
                        uint32_t a[4];
                        ldsm4t(a, ring + j * SLOT + r * 64 + (((mt * 2 + chl) ^ ((r >> 1) & 3)) << 4));
                        mma(acc[mt], a[0], a[1], a[2], a[3], xf[j * 4 + i * 2], xf[j * 4 + i * 2 + 1]);
                    }
                }
            }
            if (jq == 0) {
#pragma unroll
                for (int mt = 0; mt < 2; mt++) {
                    sm.red[w][0][mt * 16 + r4] = acc[mt][0];
                    sm.red[w][1][mt * 16 + r4] = acc[mt][1];
                    sm.red[w][0][mt * 16 + r4 + 8] = acc[mt][2];
                    sm.red[w][1][mt * 16 + r4 + 8] = acc[mt][3];
                }
            }
            bar_sync(1, 192);
            if (t < 32) {
                const int bq = t >> 4, p = t & 15;
                float q0 = 0.f, q1 = 0.f;
#pragma unroll
                for (int k = 0; k < 6; k++) { const float2 v = *reinterpret_cast<const float2*>(&sm.red[k][bq][p * 2]); q0 += v.x; q1 += v.y; }
                st_msg2(&scr->q[bq * 4096 + c * 32 + p * 2], q0, q1, tag);
            } else if (t < 44) {
                release(sm, (t >> 2) - 8);
            }
            bar_sync(1, 192);
        }
        if (t < 72) st_zero4(scr->o + (size_t)c * 288 + t * 4);
        gate(sm, lane, g0, g1);
        float* ap = scr->acc + (((c & 1) * 192 + t) >> 1) * ACC_PITCH + (t & 1) * 4;
        const int e0 = (c & 1) * 288 + w * 48 + jq * 8 + r4, e2 = (c & 1) * 288 + w * 48 + 32 + (jq & 1) * 8 + r4;
        if (c < 2) {
            const float ba = bf_lo(ldg16(b2 + e0)), bb = bf_lo(ldg16(b2 + e2));
            asm volatile("st.relaxed.gpu.global.v4.f32 [%0], {%1,%2,%3,%4};"
                         ::"l"(ap), "f"((1.f - g0) * ba), "f"((1.f - g1) * ba), "f"((1.f - ((jq & 2) ? g1 : g0)) * bb), "f"(0.f) : "memory");
        }
        uint32_t xf[6];
#pragma unroll
        for (int j = 0; j < 6; j++) xf[j] = xp[(c & 1) * 144 + (j >> 1) * 48 + w * 8 + (j & 1) * 4];
#pragma unroll 1
        for (int pass = 0; pass < npass; pass++) {
            {
                float acc[5][4] = {};
#pragma unroll
                for (int j = 0; j < 3; j++) {
                    if (pass) wait_full(sm, I_W1 + j);
                    const uint32_t base = ring + ((I_W1 + j) % NST) * SLOT + (w * 16 + rowl) * 144 + chl * 16;
#pragma unroll
                    for (int mt = 0; mt < 5; mt++) {
                        uint32_t a[4];
                        ldsm4t(a, base + mt * 32);
                        mma(acc[mt], a[0], a[1], a[2], a[3], xf[j * 2], xf[j * 2 + 1]);
                    }
                }
                if (jq == 0) {
#pragma unroll
                    for (int mt = 0; mt < 5; mt++) {
                        sm.red[w][0][mt * 16 + r4] = acc[mt][0];
                        sm.red[w][1][mt * 16 + r4] = acc[mt][1];
                        if (mt < 4) {
                            sm.red[w][0][mt * 16 + r4 + 8] = acc[mt][2];
                            sm.red[w][1][mt * 16 + r4 + 8] = acc[mt][3];
                        }
                    }
                }
                bar_sync(1, 192);
                if (t < 144) {
                    const int bb = t >= 72, k = t - bb * 72;
                    float h = 0.f;
#pragma unroll
                    for (int i = 0; i < 6; i++) h += sm.red[i][bb][k];
                    if (pass) {
                        asm volatile("{\n.reg .b32 a, b;\nmapa.shared::cluster.u32 a, %0, %3;\nmapa.shared::cluster.u32 b, %2, %3;\n"
                                     "st.async.shared::cluster.mbarrier::complete_tx::bytes.f32 [a], %1, [b];\n}"
                                     ::"r"(s2u(&sm.hx[t])), "f"(h), "r"(s2u(&sm.hbar)), "r"(~c & 1) : "memory");
                        uint32_t ok;
                        int it = 0;
                        do {
                            asm volatile("{\n.reg .pred p;\nmbarrier.try_wait.parity.acquire.cluster.shared::cta.b64 p, [%1], 0;\nselp.u32 %0, 1, 0, p;\n}"
                                         : "=r"(ok) : "r"(s2u(&sm.hbar)) : "memory");
                        } while (!ok && ++it < SPIN_LIMIT);
                    }
                    h = bf_round(h + sm.hx[t]);
                    h = fmaxf(bf_round(h + bf_lo(bias_raw)), 0.f);
                    reinterpret_cast<__nv_bfloat16*>(sm.hs)[t] = __float2bfloat16_rn(h * h);
                }
                bar_sync(1, 192);
            }
            float acc[3][4] = {};
            {
                uint32_t hb[9];
#pragma unroll
                for (int k = 0; k < 9; k++) hb[k] = sm.hs[r4 & 1][k * 4 + jq];
#pragma unroll
                for (int j = 0; j < 3; j++) {
                    if (pass) wait_full(sm, I_W2 + j);
#pragma unroll
                    for (int i = 0; i < 3; i++) {
                        const int mt = w * 3 + i;
#pragma unroll
                        for (int ks = 0; ks < 2; ks++) {
                            const int r = ks ? 16 + (lane & 7) : rowl;
                            uint32_t a[4];
                            ldsm4t(a, ring + ((I_W2 + j) % NST) * SLOT + (mt >> 1) * 1536 + r * 64 + ((((mt & 1) * 2 + chl) ^ ((r >> 1) & 3)) << 4));
                            mma(acc[i], a[0], a[1], a[2], a[3], hb[j * 3 + ks * 2], ks ? 0u : hb[j * 3 + 1]);
                        }
                    }
                }
#pragma unroll
                for (int i = 0; i < 3; i++) { acc[i][0] *= 1.f - g0; acc[i][1] *= 1.f - g1; acc[i][2] *= 1.f - g0; acc[i][3] *= 1.f - g1; }
            }
            if (pass) mbar_wait(s2u(&sm.obar), 0);
            uint32_t ob[8];
#pragma unroll
            for (int k = 0; k < 8; k++) ob[k] = sm.os[r4 & 1][k * 4 + jq];
#pragma unroll
            for (int j = 0; j < 4; j++) {
                if (pass) wait_full(sm, I_WO + j);
#pragma unroll
                for (int i = 0; i < 3; i++) {
                    const int mt = w * 3 + i;
                    uint32_t a[4];
                    ldsm4t(a, ring + ((I_WO + j) % NST) * SLOT + (mt >> 1) * 1024 + rowl * 64 + ((((mt & 1) * 2 + chl) ^ ((rowl >> 1) & 3)) << 4));
                    mma(acc[i], a[0], a[1], a[2], a[3], ob[j * 2], ob[j * 2 + 1]);
                }
            }
            {
                const float u0 = (jq & 1) ? acc[0][2] : acc[0][0], u1 = (jq & 1) ? acc[0][3] : acc[0][1];
                const float v0 = (jq & 1) ? acc[1][2] : acc[1][0], v1 = (jq & 1) ? acc[1][3] : acc[1][1];
                const float p0 = (jq & 2) ? v0 : u0, p1 = (jq & 2) ? v1 : u1;
                const float p2 = (jq & 1) ? ((jq & 2) ? acc[2][3] : acc[2][2]) : ((jq & 2) ? acc[2][1] : acc[2][0]);
                float s0 = 0.f, s1 = 0.f, s2 = 0.f, n = 0.f;
                asm volatile("{\n.reg .pred p;\nsetp.ne.u32 p, %9, 0;\n@p atom.relaxed.gpu.global.add.v4.f32 {%0,%1,%2,%3}, [%4], {%5,%6,%7,%8};\n}"
                             : "+f"(s0), "+f"(s1), "+f"(s2), "+f"(n) : "l"(ap), "f"(p0), "f"(p1), "f"(p2), "f"(1.f), "r"(pass) : "memory");
                if (n == (float)(NCTA / 2 - 1)) {
                    out[e0] = __float2bfloat16_rn(s0 + p0);
                    out[e0 + D_MODEL] = __float2bfloat16_rn(s1 + p1);
                    out[e2 + (jq >> 1) * D_MODEL] = __float2bfloat16_rn(s2 + p2);
                }
            }
            if (!pass) {
                bar_sync(1, 192);
                if (t == 0) asm volatile("red.release.gpu.global.add.u32 [%0], 1;" ::"l"(&scr->ready) : "memory");
            }
        }
        return;
    }

    gate(sm, lane, g0, g1);
#pragma unroll 1
    for (int pass = 0; pass < npass; pass++) {
        float o[8][4] = {};
        float m = -INFINITY, l = 0.f;
        if (pass) {
            const float* qp = scr->q + ((c >> 2) & 1) * 4096 + (c >> 3) * 256 + t * 2;
            uint2 v;
            int it = 0;
            wait_full(sm, I_QPOLL);
            do { v = ld_msg2(qp); } while (!ok2(v, tag) && ++it < SPIN_LIMIT);
            (&sm.qs[0][0])[t] = pack_bf16(__uint_as_float(v.x), __uint_as_float(v.y));
            bar_sync(3, 128);
            uint32_t qf[16];
#pragma unroll
            for (int ks = 0; ks < 8; ks++) {
                qf[2 * ks] = lane < 8 ? sm.qs[lane >> 2][ks * 8 + (lane & 3)] : 0u;
                qf[2 * ks + 1] = lane < 8 ? sm.qs[lane >> 2][ks * 8 + 4 + (lane & 3)] : 0u;
            }
            const int key = w * 16 + rowl;
            const uint32_t off = key * 128;
            const int sw = key & 7;
#pragma unroll 1
            for (int tl = 0; tl < 16; tl++) {
                const int ik = I_K + tl;
                wait_full(sm, ik);
                const uint32_t kb = ring + (ik % NST) * SLOT + off;
                float s[2][2][4] = {};
#pragma unroll
                for (int ks = 0; ks < 8; ks++) {
                    uint32_t kf[4];
                    ldsm4(kf, kb + (ks >> 2) * 8192 + ((((ks & 3) * 2 + chl) ^ sw) << 4));
                    mma(s[0][ks & 1], qf[2 * ks], 0u, qf[2 * ks + 1], 0u, kf[0], kf[1]);
                    mma(s[1][ks & 1], qf[2 * ks], 0u, qf[2 * ks + 1], 0u, kf[2], kf[3]);
                }
                __syncwarp();
                if (lane == 0) release(sm, ik);
                const float4 sv = make_float4(s[0][0][0] + s[0][1][0], s[0][0][1] + s[0][1][1], s[1][0][0] + s[1][1][0], s[1][0][1] + s[1][1][1]);
                m = fmaxf(m, fmaxf(fmaxf(sv.x, sv.y), fmaxf(sv.z, sv.w)));
                if (lane < 8) sm.sc[w][tl][lane] = sv;
            }
            m = fmaxf(m, __shfl_xor_sync(~0u, m, 1));
            m = fmaxf(m, __shfl_xor_sync(~0u, m, 2));
            m = __shfl_sync(~0u, m, lane & 7);
            if (t == 0) {
                uint32_t seen;
                it = 0;
                do {
                    asm volatile("ld.acquire.gpu.global.u32 %0, [%1];" : "=r"(seen) : "l"(&scr->ready) : "memory");
                } while ((int)(seen - (epoch + 1u) * NCTA) < 0 && ++it < SPIN_LIMIT);
            }
            __syncwarp();
            const float ms = m * SC;
#pragma unroll 1
            for (int tl = 0; tl < 16; tl++) {
                const int iv = I_V + tl;
                const float4 sv = sm.sc[w][tl][lane & 7];
                const uint32_t p0 = pack_bf16(ex2(fmaf(sv.x, SC, -ms)), ex2(fmaf(sv.y, SC, -ms)));
                const uint32_t p1 = pack_bf16(ex2(fmaf(sv.z, SC, -ms)), ex2(fmaf(sv.w, SC, -ms)));
                l += (bf_lo(p0) + bf_hi(p0)) + (bf_lo(p1) + bf_hi(p1));
                wait_full(sm, iv);
                const uint32_t vb = ring + (iv % NST) * SLOT + off;
#pragma unroll
                for (int mt = 0; mt < 8; mt++) {
                    uint32_t vf[4];
                    ldsm4t(vf, vb + (mt >> 2) * 8192 + ((((mt & 3) * 2 + chl) ^ sw) << 4));
                    mma(o[mt], vf[0], vf[1], vf[2], vf[3], p0, p1);
                }
                __syncwarp();
                if (lane == 0) release(sm, iv);
            }
        }
        l += __shfl_xor_sync(~0u, l, 1);
        l += __shfl_xor_sync(~0u, l, 2);
        if (lane == 0 || lane == 4) { sm.ml[w][lane >> 2][0] = m; sm.ml[w][lane >> 2][1] = l; }
        if ((lane & 3) == 0) {
#pragma unroll
            for (int mt = 0; mt < 8; mt++) {
                sm.ocomb[w][0][mt * 16 + r4] = o[mt][0];
                sm.ocomb[w][1][mt * 16 + r4] = o[mt][1];
                sm.ocomb[w][0][mt * 16 + r4 + 8] = o[mt][2];
                sm.ocomb[w][1][mt * 16 + r4 + 8] = o[mt][3];
            }
        }
        bar_sync(3, 128);
        {
            const int h = t >> 6, d = (t & 63) * 2;
            const float M = fmaxf(fmaxf(sm.ml[0][h][0], sm.ml[1][h][0]), fmaxf(sm.ml[2][h][0], sm.ml[3][h][0]));
            float L = 0.f, O0 = 0.f, O1 = 0.f;
#pragma unroll
            for (int k = 0; k < 4; k++) {
                const float sc = ex2((sm.ml[k][h][0] - M) * SC);
                const float2 ov = *reinterpret_cast<const float2*>(&sm.ocomb[k][h][d]);
                L = fmaf(sc, sm.ml[k][h][1], L);
                O0 = fmaf(sc, ov.x, O0);
                O1 = fmaf(sc, ov.y, O1);
            }
            float* dst = scr->o + ((size_t)((c >> 3) * 4 + w) * 8 + (c & 7)) * 72;
            st_val2_if(dst + lane * 2, O0, O1, pass);
            st_val2_if(dst + 64 + lane * 2, M, L, pass && lane < 4);
        }
        {
            const int bb = t >> 6, col = t & 60;
            const float* src = scr->o + ((size_t)(c >> 1) * 8 + bb * 4 + jq) * 72;
            uint4 v = make_uint4(!pass, 1u, 1u, 1u);
            uint2 ml = make_uint2(!pass, 1u);
            int it = 0;
            if (pass) wait_full(sm, I_OPOLL);
            do {
                ld_msg4_if(v, src + col, !val4(v));
                ld_msg2_if(ml, src + 64, !val2(ml));
            } while (!(val4(v) && val2(ml)) && ++it < SPIN_LIMIT);
            __syncwarp();
            const float mm = __uint_as_float(ml.x);
            float M = fmaxf(mm, __shfl_xor_sync(~0u, mm, 1));
            M = fmaxf(M, __shfl_xor_sync(~0u, M, 2));
            const float f = ex2((mm - M) * SC);
            float L = f * __uint_as_float(ml.y);
            const bool hi = jq & 1;
            float o0 = f * __uint_as_float(hi ? v.z : v.x), o1 = f * __uint_as_float(hi ? v.w : v.y);
            o0 += __shfl_xor_sync(~0u, f * __uint_as_float(hi ? v.x : v.z), 1);
            o1 += __shfl_xor_sync(~0u, f * __uint_as_float(hi ? v.y : v.w), 1);
            L += __shfl_xor_sync(~0u, L, 1);
            o0 += __shfl_xor_sync(~0u, o0, 2);
            o1 += __shfl_xor_sync(~0u, o1, 2);
            L += __shfl_xor_sync(~0u, L, 2);
            const float inv = (bb ? g1 : g0) * rcp(L);
            if (pass) {
                if (jq < 2) sm.os[bb][(col >> 1) + jq] = pack_bf16(o0 * inv, o1 * inv);
                mbar_arrive(s2u(&sm.obar));
            }
        }
    }
}

typedef CUresult (*EncFn)(CUtensorMap*, CUtensorMapDataType, cuuint32_t, void*, const cuuint64_t*, const cuuint64_t*,
                          const cuuint32_t*, const cuuint32_t*, CUtensorMapInterleave, CUtensorMapSwizzle,
                          CUtensorMapL2promotion, CUtensorMapFloatOOBfill);

}

extern "C" void kernel_launch(void* const* d_in, const int* in_sizes, int n_in, void* d_out, int out_size) {
    (void)in_sizes; (void)n_in; (void)out_size;
    EncFn enc = nullptr;
    cudaDriverEntryPointQueryResult qr;
    cudaGetDriverEntryPoint("cuTensorMapEncodeTiled", (void**)&enc, cudaEnableDefault, &qr);
    Maps maps;
    const CUtensorMapL2promotion pr = CU_TENSOR_MAP_L2_PROMOTION_L2_256B;
    auto mk = [&](int i, void* p, uint64_t d0, uint64_t d1, uint64_t d2, uint64_t s1, uint64_t s2, uint32_t b0, uint32_t b1, uint32_t b2,
                  CUtensorMapSwizzle sw) {
        cuuint64_t d[3] = {d0, d1, d2}, s[2] = {s1, s2};
        cuuint32_t b[3] = {b0, b1, b2}, e[3] = {1, 1, 1};
        enc(&maps.m[i], CU_TENSOR_MAP_DATA_TYPE_BFLOAT16, 3, p, d, s, b, e, CU_TENSOR_MAP_INTERLEAVE_NONE, sw, pr,
            CU_TENSOR_MAP_FLOAT_OOB_FILL_NONE);
    };
    mk(0, d_in[3], 4096, 576, 1, 8192, 8192 * 576, 32, 192, 1, CU_TENSOR_MAP_SWIZZLE_64B);
    mk(1, d_in[1], 64, 32ull * SK, 2, 256, 128, 64, 64, 2, CU_TENSOR_MAP_SWIZZLE_128B);
    mk(2, d_in[2], 64, 32ull * SK, 2, 256, 128, 64, 64, 2, CU_TENSOR_MAP_SWIZZLE_128B);
    mk(3, d_in[6], 4608, 576, 1, 9216, 9216 * 576, 72, 96, 1, CU_TENSOR_MAP_SWIZZLE_NONE);
    mk(4, d_in[8], 32, 4608, 18, 1152, 64, 32, 24, 9, CU_TENSOR_MAP_SWIZZLE_64B);
    mk(5, d_in[4], 32, 4096, 18, 1152, 64, 32, 16, 9, CU_TENSOR_MAP_SWIZZLE_64B);
    const int smem = NST * SLOT + 1024;
    cudaFuncSetAttribute(fused_kernel, cudaFuncAttributeMaxDynamicSharedMemorySize, smem);
    void* scr = nullptr;
    cudaGetSymbolAddress(&scr, g_scr);
    fused_kernel<<<NCTA, NTHR, smem, cudaStreamPerThread>>>(
        (const char*)d_in[3], (const __nv_bfloat16*)d_in[0], (const __nv_bfloat16*)d_in[7], (const __nv_bfloat16*)d_in[9],
        (const __nv_bfloat16*)d_in[10], (__nv_bfloat16*)d_out, (Scratch*)scr, maps);
}
```

```cpp
#include <cuda_runtime.h>
#include <cuda_bf16.h>
#include <cuda.h>
#include <stdint.h>

namespace {

constexpr int D_MODEL = 576;
constexpr int SK = 32768;
constexpr int WIN = 4096;
constexpr int NCTA = 128;
constexpr int SLOT = 16384;
constexpr int NST = 6;
constexpr int INFL = 4;
constexpr int LO = 2, HI = 5, HIT = 7;
constexpr int PACE = 20841;
constexpr int LEAD = 1400;
constexpr int I_K = 3, I_W1 = 19, I_V = 22, I_W2 = 38, I_WO = 41, NITEM = 45;
constexpr int NTHR = 320;
constexpr int SM_HEAD = 17408;
constexpr int SPIN_LIMIT = 1 << 17;

struct Scratch {
    float acc[288 * 32];
    unsigned ready, pad[3];
};
__device__ __align__(128) Scratch g_scr;

struct __align__(16) Smem {
    uint4 tab[NITEM][2];
    uint2 tab2[NITEM + 1];
    uint64_t full[NITEM];
    uint64_t empty[NST];
    uint64_t xb[6];
    float2 g;
    uint4 p[128][2];
    float2 qin[8][32];
    float2 hin[8][36];
    float4 oin[4][17];
    float2 mx[4], ls[4];
    uint32_t qs[128];
    uint32_t hs[2][72];
    uint32_t os[2][68];
};
static_assert(sizeof(Smem) <= SM_HEAD, "");

__device__ __forceinline__ uint32_t s2u(const void* p) { return (uint32_t)__cvta_generic_to_shared(p); }
__device__ __forceinline__ void mbar_init(uint32_t a, int c) { asm volatile("mbarrier.init.shared.b64 [%0], %1;" ::"r"(a), "r"(c) : "memory"); }
__device__ __forceinline__ void mbar_expect(uint32_t a, uint32_t b) { asm volatile("mbarrier.arrive.expect_tx.shared.b64 _, [%0], %1;" ::"r"(a), "r"(b) : "memory"); }
__device__ __forceinline__ void mbar_wait(uint32_t a, uint32_t ph) {
    uint32_t ok;
    int it = 0;
    do {
        asm volatile("{\n.reg .pred p;\nmbarrier.try_wait.parity.shared.b64 p, [%1], %2;\nselp.u32 %0, 1, 0, p;\n}" : "=r"(ok) : "r"(a), "r"(ph) : "memory");
    } while (!ok && ++it < SPIN_LIMIT);
}
__device__ __forceinline__ void wait_msg(Smem& sm, int i) {
    uint32_t ok;
    int it = 0;
    do {
        asm volatile("{\n.reg .pred p;\nmbarrier.try_wait.parity.acquire.cluster.shared::cta.b64 p, [%1], 0;\nselp.u32 %0, 1, 0, p;\n}"
                     : "=r"(ok) : "r"(s2u(&sm.xb[i])) : "memory");
    } while (!ok && ++it < SPIN_LIMIT);
}
__device__ __forceinline__ void send1(Smem& sm, int i, const void* dst, int rank, uint32_t v, uint32_t pred) {
    asm volatile("{\n.reg .pred p;\n.reg .b32 a, b;\nsetp.ne.u32 p, %4, 0;\nmapa.shared::cluster.u32 a, %0, %2;\nmapa.shared::cluster.u32 b, %1, %2;\n"
                 "@p st.async.shared::cluster.mbarrier::complete_tx::bytes.u32 [a], %3, [b];\n}"
                 ::"r"(s2u(dst)), "r"(s2u(&sm.xb[i])), "r"(rank), "r"(v), "r"(pred) : "memory");
}
__device__ __forceinline__ void send2(Smem& sm, int i, const void* dst, int rank, float v0, float v1, uint32_t pred) {
    asm volatile("{\n.reg .pred p;\n.reg .b32 a, b;\nsetp.ne.u32 p, %5, 0;\nmapa.shared::cluster.u32 a, %0, %2;\nmapa.shared::cluster.u32 b, %1, %2;\n"
                 "@p st.async.shared::cluster.mbarrier::complete_tx::bytes.v2.f32 [a], {%3, %4}, [b];\n}"
                 ::"r"(s2u(dst)), "r"(s2u(&sm.xb[i])), "r"(rank), "f"(v0), "f"(v1), "r"(pred) : "memory");
}
__device__ __forceinline__ void scatter(Smem& sm, int i, const void* dst, int j, const float* v, int lane, uint32_t pred) {
    const bool odd = lane & 4;
    const float y0 = __shfl_xor_sync(~0u, odd ? v[0] : v[2], 4), y1 = __shfl_xor_sync(~0u, odd ? v[1] : v[3], 4);
    send2(sm, i, dst, j, odd ? y0 : v[0], odd ? v[2] : y0, pred);
    send2(sm, i, dst, j + 4, odd ? y1 : v[1], odd ? v[3] : y1, pred);
}
template <int P> __device__ __forceinline__ float2 sum8(const float2* p) {
    float2 v[8];
#pragma unroll
    for (int k = 0; k < 8; k++) v[k] = p[k * P];
    return make_float2(((v[0].x + v[1].x) + (v[2].x + v[3].x)) + ((v[4].x + v[5].x) + (v[6].x + v[7].x)),
                       ((v[0].y + v[1].y) + (v[2].y + v[3].y)) + ((v[4].y + v[5].y) + (v[6].y + v[7].y)));
}
__device__ __forceinline__ void tma3d_ef(uint32_t dst, const CUtensorMap* m, int c0, int c1, int c2, uint32_t bar, uint64_t pol) {
    asm volatile("cp.async.bulk.tensor.3d.shared::cluster.global.mbarrier::complete_tx::bytes.L2::cache_hint [%0], [%1, {%3, %4, %5}], [%2], %6;"
                 ::"r"(dst), "l"(m), "r"(bar), "r"(c0), "r"(c1), "r"(c2), "l"(pol) : "memory");
}
__device__ __forceinline__ void ldsm4(uint32_t* r, uint32_t a) {
    asm volatile("ldmatrix.sync.aligned.m8n8.x4.shared.b16 {%0,%1,%2,%3}, [%4];" : "=r"(r[0]), "=r"(r[1]), "=r"(r[2]), "=r"(r[3]) : "r"(a) : "memory");
}
__device__ __forceinline__ void ldsm4t(uint32_t* r, uint32_t a) {
    asm volatile("ldmatrix.sync.aligned.m8n8.x4.trans.shared.b16 {%0,%1,%2,%3}, [%4];" : "=r"(r[0]), "=r"(r[1]), "=r"(r[2]), "=r"(r[3]) : "r"(a) : "memory");
}
__device__ __forceinline__ void mma(float* c, uint32_t a0, uint32_t a1, uint32_t a2, uint32_t a3, uint32_t b0, uint32_t b1) {
    asm volatile("mma.sync.aligned.m16n8k16.row.col.f32.bf16.bf16.f32 {%0,%1,%2,%3}, {%4,%5,%6,%7}, {%8,%9}, {%0,%1,%2,%3};"
                 : "+f"(c[0]), "+f"(c[1]), "+f"(c[2]), "+f"(c[3]) : "r"(a0), "r"(a1), "r"(a2), "r"(a3), "r"(b0), "r"(b1));
}
__device__ __forceinline__ uint32_t pack_bf16(float lo, float hi) {
    uint32_t r;
    asm("cvt.rn.bf16x2.f32 %0, %1, %2;" : "=r"(r) : "f"(hi), "f"(lo));
    return r;
}
__device__ __forceinline__ float bf_lo(uint32_t v) { return __uint_as_float(v << 16); }
__device__ __forceinline__ float bf_hi(uint32_t v) { return __uint_as_float(v & 0xffff0000u); }
__device__ __forceinline__ float ex2(float v) { float r; asm("ex2.approx.ftz.f32 %0, %1;" : "=f"(r) : "f"(v)); return r; }
__device__ __forceinline__ float rcp(float v) { float r; asm("rcp.approx.ftz.f32 %0, %1;" : "=f"(r) : "f"(v)); return r; }
__device__ __forceinline__ void bar_sync(int id, int n) { asm volatile("bar.sync %0, %1;" ::"r"(id), "r"(n) : "memory"); }
__device__ __forceinline__ void wait_full(Smem& sm, int i) { mbar_wait(s2u(&sm.full[i]), 0); }
__device__ __forceinline__ void release(Smem& sm, int slot, int n, uint32_t pred) {
    __syncwarp();
    asm volatile("{\n.reg .pred p;\nsetp.ne.u32 p, %2, 0;\n@p mbarrier.arrive.shared.b64 _, [%0], %1;\n}" ::"r"(s2u(&sm.empty[slot])), "r"(n), "r"(pred) : "memory");
}

__device__ __forceinline__ uint32_t ldg32(const void* p) {
    uint32_t v;
    asm volatile("ld.global.nc.u32 %0, [%1];" : "=r"(v) : "l"(p));
    return v;
}

struct Maps { CUtensorMap m[6]; };

__global__ void __cluster_dims__(8, 1, 1) __launch_bounds__(NTHR, 2)
fused_kernel(const char* __restrict__ wq, const __nv_bfloat16* __restrict__ x, const __nv_bfloat16* __restrict__ b1,
             const __nv_bfloat16* __restrict__ b2, const __nv_bfloat16* __restrict__ gate_w,
             __nv_bfloat16* __restrict__ out, Scratch* __restrict__ scr, const __grid_constant__ Maps maps) {
    extern __shared__ __align__(1024) unsigned char smem_raw[];
    Smem& sm = *reinterpret_cast<Smem*>(smem_raw);
    asm volatile("{\n.reg .pred p;\n.reg .b32 t;\n.reg .b64 a;\nmov.u32 t, %%ctaid.x;\nmad.wide.u32 a, t, 36864, %0;\n"
                 "mov.u32 t, %%tid.x;\nsetp.eq.u32 p, t, 0;\n@p cp.async.bulk.prefetch.L2.global [a], 36864;\n}" ::"l"(wq) : "memory");
    const uint32_t ring = s2u(smem_raw) + SM_HEAD;
    const int tid = threadIdx.x, lane = tid & 31;
    const int c = blockIdx.x;
    const int warp = __shfl_sync(~0u, tid >> 5, 0);

    if (tid == 0) {
#pragma unroll
        for (int i = 0; i < 6; i++) asm volatile("prefetch.tensormap [%0];" ::"l"(&maps.m[i]) : "memory");
#pragma unroll
        for (int i = 0; i < NST; i++) mbar_init(s2u(&sm.full[i]), 1);
#pragma unroll
        for (int i = 0; i < NST; i++) mbar_init(s2u(&sm.empty[i]), 20);
        asm volatile("fence.proxy.async.shared::cta;" ::: "memory");
    }
    if (tid < NITEM) {
        const int i = tid;
        const uint32_t bars = s2u(sm.full);
        const bool q = i < 3, w1 = i >= I_W1 && i < I_W1 + 3, wo = i >= I_WO, w2o = i >= I_W2, kv = !(q || w1 || w2o), v = i >= I_V;
        const int k = i - (q ? 0 : w1 ? I_W1 : wo ? I_WO : w2o ? I_W2 : v ? I_V : I_K);
        const int kvrow = ((((c >> 2) & 1) * 16 + (c >> 3)) * SK) + (SK - WIN) + (c & 3) * 64;
        const uint32_t c0 = w2o ? (c & 3) * 144 : 0, c2 = (c >> 3) * (q ? 4 : w1 ? 9 : 0);
        const uint32_t c1 = k * (kv ? 256 : wo ? 32 : w2o ? 48 : 24) + (kv ? kvrow : w2o ? (c >> 2) * (wo ? 128 : 144) : (c & 7) * 72);
        const uint32_t bytes = kv ? 16384 : q ? 12288 : wo ? 9216 : 13824;
        const uint32_t map = q ? 0 : w1 ? 3 : wo ? 5 : w2o ? 4 : v ? 2 : 1;
        const int j = i - (i > I_WO ? HIT : HI);
        const int j2 = i < INFL ? -1 : i - LO;
        const int cum = (q ? 0 : w1 ? 72 + (I_W1 - 3) * 32 : wo ? 72 + 1024 + 162 : w2o ? 72 + 1024 + 81 : v ? 72 + 512 + (I_V - 19) * 27 : 72 + (I_K - 3) * 27) * 512 + (k + 1) * bytes;
        uint32_t now;
        asm volatile("mov.u32 %0, %%globaltimer_lo;" : "=r"(now));
        const int lap = (i * 43) >> 8, slot = i - lap * NST;
        const uint32_t fl = (j < 0) | ((~lap & 1) << 1) | ((j2 < 0) << 2) | (map << 10);
        sm.tab[i][0] = make_uint4(ring + slot * (i > I_WO ? 9216 : SLOT), bars + i * 8, c0, c1);
        sm.tab[i][1] = make_uint4(c2, bytes, bars + (j < 0 ? i : j) * 8, fl | ((bars + (NITEM + slot - (i == NITEM - 1)) * 8) << 16));
        sm.tab2[i] = make_uint2(bars + (j2 < 0 ? i : j2) * 8, now + (((cum >> 9) * PACE) >> 10) - LEAD);
    }
    int warp2;
    asm volatile("mov.u32 %0, %1;" : "=r"(warp2) : "r"(warp));
    if (warp2 == 0) {
        asm volatile("bar.arrive 0, %0;" ::"n"(NTHR - 128) : "memory");
        asm volatile("bar.arrive 2, 192;" ::: "memory");
        __syncwarp();
        if (lane != 0) return;
        {
            uint64_t pol;
            asm volatile("createpolicy.fractional.L2::evict_first.b64 %0, 1.0;" : "=l"(pol));
#pragma unroll 1
            for (int i = 0; i < NITEM; i++) {
                const uint4 a = sm.tab[i][0], b = sm.tab[i][1];
                const char* map = reinterpret_cast<const char*>(&maps) + ((b.w >> 3) & 0x380);
                asm volatile("" : "+l"(map));
                mbar_wait((b.w >> 16) | (a.y & 0xff000000u), (b.w >> 1) & 1);
                mbar_expect(a.y, b.y);
                mbar_wait(b.z, b.w & 1);
                {
                    const uint2 d = sm.tab2[i];
                    uint32_t go;
                    int it = 0;
                    do {
                        asm volatile("{\n.reg .pred p;\n.reg .b32 t;\nmov.u32 t, %%globaltimer_lo;\nmbarrier.test_wait.parity.shared.b64 p, [%1], %2;\n"
                                     "sub.s32 t, t, %3;\nsetp.ge.or.s32 p, t, 0, p;\nselp.u32 %0, 1, 0, p;\n}"
                                     : "=r"(go) : "r"(d.x), "r"((b.w >> 2) & 1), "r"(d.y) : "memory");
                    } while (!go && ++it < SPIN_LIMIT);
                }
                tma3d_ef(a.x, reinterpret_cast<const CUtensorMap*>(map), a.z, a.w, b.x, a.y, pol);
                if (i == INFL - 1) asm volatile("barrier.cluster.arrive.relaxed;" ::: "memory");
            }
        }
    }
    if (warp == 0) return;

    const int t = tid - (warp > 4 ? 160 : 32), w = warp - (warp > 4 ? 5 : 1);
    const int rowl = ((lane >> 4) << 3) + (lane & 7);
    const int chl = (lane >> 3) & 1;
    const int r4 = lane >> 2, jq = lane & 3;
    int npass;
    asm volatile("mov.u32 %0, 2;" : "=r"(npass));
    if (tid == 319) {
#pragma unroll
        for (int i = 0; i < 6; i++) mbar_init(s2u(&sm.xb[i]), 1);
        asm volatile("fence.mbarrier_init.release.cluster;" ::: "memory");
    }
    __syncwarp();
    asm volatile("barrier.cluster.arrive.relaxed.aligned;" ::: "memory");

    if (warp > 4) {
        const int hd = (t * 57) >> 11, hi = t - hd * 36;
        const int pr = jq * 8 + (r4 & 1) * 4 + (r4 >> 1);
        uint32_t xf[9], epoch = 0;
#pragma unroll
        for (int k = 0; k < 9; k++) xf[k] = ldg32(x + (r4 & 1) * D_MODEL + (c & 7) * 72 + k * 8 + jq * 2);
        const uint32_t bias = ldg32(b1 + (c >> 3) * 288 + (c & 3) * 72 + hi * 2);
        if (w == 4) {
            if (lane == 31) {
                asm volatile("ld.relaxed.gpu.global.u32 %0, [%1];" : "=r"(epoch) : "l"(&scr->ready));
                mbar_expect(s2u(&sm.xb[0]), 2048);
                mbar_expect(s2u(&sm.xb[1]), 512);
                mbar_expect(s2u(&sm.xb[2]), 2304);
                mbar_expect(s2u(&sm.xb[3]), 576);
                mbar_expect(s2u(&sm.xb[4]), 1088);
                mbar_expect(s2u(&sm.xb[5]), 512);
#pragma unroll 1
                for (int i = NST; i < NITEM; i++) mbar_init(s2u(&sm.full[i]), 1);
                asm volatile("fence.proxy.async.shared::cta;" ::: "memory");
            }
            __syncwarp();
            asm volatile("bar.arrive 2, 192;" ::: "memory");
        }
        bar_sync(0, NTHR - 128);
        asm volatile("barrier.cluster.wait.aligned;" ::: "memory");
        if (w == 4) {
            float s0 = 0.f, s1 = 0.f;
#pragma unroll
            for (int i = 0; i < 9; i++) {
                const uint32_t gv = ldg32(gate_w + i * 64 + lane * 2), a = ldg32(x + i * 64 + lane * 2), b = ldg32(x + D_MODEL + i * 64 + lane * 2);
                s0 = fmaf(bf_lo(gv), bf_lo(a), fmaf(bf_hi(gv), bf_hi(a), s0));
                s1 = fmaf(bf_lo(gv), bf_lo(b), fmaf(bf_hi(gv), bf_hi(b), s1));
            }
#pragma unroll
            for (int o = 16; o; o >>= 1) { s0 += __shfl_xor_sync(~0u, s0, o); s1 += __shfl_xor_sync(~0u, s1, o); }
            sm.g = make_float2(1.f / (1.f + __expf(-s0)), 1.f / (1.f + __expf(-s1)));
        }
        if (w < 4) {
            float acc[4][4] = {};
#pragma unroll
            for (int j = 0; j < 3; j++) {
                wait_full(sm, j);
#pragma unroll
                for (int mt = 0; mt < 4; mt++) {
#pragma unroll
                    for (int ks = 0; ks < 2; ks++) {
                        const int r = ks ? 16 + (lane & 7) : rowl;
                        uint32_t a[4];
                        ldsm4t(a, ring + j * SLOT + w * 3072 + r * 128 + (((mt * 2 + chl) ^ (r & 7)) << 4));
                        mma(acc[mt], a[0], a[1], a[2], a[3], xf[j * 3 + ks * 2], ks ? 0u : xf[j * 3 + 1]);
                    }
                }
                release(sm, j, 5, lane == 0);
            }
            float v[4];
#pragma unroll
            for (int e = 0; e < 4; e++) v[e] = (jq & 2) ? ((jq & 1) ? acc[3][e] : acc[2][e]) : ((jq & 1) ? acc[1][e] : acc[0][e]);
            scatter(sm, 0, &sm.qin[c & 7][pr], w, v, lane, 1);
        }
        bar_sync(1, 160);
        const float g0 = sm.g.x, g1 = sm.g.y;
        const int ec = (c & 3) * 144 + w * 32 + jq * 8 + r4;
        const bool live = w * 4 + jq < 18;
        float* ap = scr->acc + (ec >> 1) * 32 + (r4 & 1) * 4;
        if (c < 4 && live) {
            uint32_t bv;
            asm volatile("ld.global.nc.u16 %0, [%1];" : "=r"(bv) : "l"(b2 + ec));
            asm volatile("st.relaxed.gpu.global.v4.f32 [%0], {%1,%2,%3,%3};" ::"l"(ap), "f"((1.f - g0) * bf_lo(bv)), "f"((1.f - g1) * bf_lo(bv)), "f"(0.f) : "memory");
        }
#pragma unroll 1
        for (int pass = 0; pass < npass; pass++) {
            {
                float acc[4][4] = {};
#pragma unroll
                for (int j = 0; j < 3; j++) {
                    if (pass) wait_full(sm, I_W1 + j);
#pragma unroll
                    for (int mt = 0; mt < 4; mt++) {
                        if (mt > 1 && w == 4) continue;
#pragma unroll
                        for (int ks = 0; ks < 2; ks++) {
                            const int r = ks ? 16 + (lane & 7) : rowl;
                            uint32_t a[4];
                            ldsm4t(a, ring + ((I_W1 + j) % NST) * SLOT + (w * 2 + (mt >> 1)) * 1536 + r * 64 + ((((mt & 1) * 2 + chl) ^ ((r >> 1) & 3)) << 4));
                            mma(acc[mt], a[0], a[1], a[2], a[3], xf[j * 3 + ks * 2], ks ? 0u : xf[j * 3 + 1]);
                        }
                    }
                    release(sm, (I_W1 + j) % NST, 4, pass && lane == 0);
                }
                float v[4];
#pragma unroll
                for (int e = 0; e < 4; e++) v[e] = (jq & 2) ? ((jq & 1) ? acc[3][e] : acc[2][e]) : ((jq & 1) ? acc[1][e] : acc[0][e]);
                const int cp = w * 32 + pr, cj = (cp * 57) >> 11;
                scatter(sm, 2, &sm.hin[c & 7][cp - cj * 36], cj & 3, v, lane, pass && live);
                if (pass) wait_msg(sm, 2);
                const float2 hv = sum8<36>(&sm.hin[0][hi]);
                const uint32_t hr = pack_bf16(hv.x, hv.y), hb = pack_bf16(bf_lo(hr) + bf_lo(bias), bf_hi(hr) + bf_hi(bias));
                const float h0 = fmaxf(bf_lo(hb), 0.f), h1 = fmaxf(bf_hi(hb), 0.f);
                send1(sm, 3, &sm.hs[(c >> 2) & 1][(c & 1) * 36 + hi], (c & 2) * 2 + (hd & 3), pack_bf16(h0 * h0, h1 * h1), pass && t < 144);
                if (pass && t == 159) {
                    uint32_t seen;
                    int it = 0;
                    do {
                        asm volatile("ld.acquire.gpu.global.u32 %0, [%1];" : "=r"(seen) : "l"(&scr->ready) : "memory");
                    } while ((int)(seen - (epoch / NCTA + 1u) * NCTA) < 0 && ++it < SPIN_LIMIT);
                }
                __syncwarp();
                bar_sync(1, 160);
                if (!pass && t == 159) asm volatile("red.release.gpu.global.add.u32 [%0], 1;" ::"l"(&scr->ready) : "memory");
            }
            {
                float f0, f1;
                const uint32_t aoff = ring + rowl * 288 + w * 64 + ((chl ^ (lane >> 2)) & 1) * 16;
                const bool bz = (r4 ^ jq) & 2;
                {
                    if (pass) wait_msg(sm, 3);
                    float acc[2][4] = {};
                    uint32_t hb[18];
#pragma unroll
                    for (int k = 0; k < 18; k++) hb[k] = bz ? 0u : sm.hs[r4 & 1][k * 4 + jq];
#pragma unroll
                    for (int j = 0; j < 3; j++) {
                        if (pass) wait_full(sm, I_W2 + j);
#pragma unroll
                        for (int ks = 0; ks < 3; ks++) {
#pragma unroll
                            for (int i = 0; i < 2; i++) {
                                if (i && w == 4) continue;
                                uint32_t a[4];
                                ldsm4t(a, ((I_W2 + j) % NST) * SLOT + ks * 4608 + i * 32 + aoff);
                                mma(acc[i], a[0], a[1], a[2], a[3], hb[j * 6 + ks * 2], hb[j * 6 + ks * 2 + 1]);
                            }
                        }
                    }
#pragma unroll
                    for (int e = 0; e < 4; e++) acc[0][e] = (jq & 2) ? acc[1][e] : acc[0][e];
                    f0 = (1.f - g0) * (acc[0][0] + __shfl_xor_sync(~0u, acc[0][2], 1));
                    f1 = (1.f - g1) * (acc[0][1] + __shfl_xor_sync(~0u, acc[0][3], 1));
                }
                if (pass) wait_msg(sm, 5);
                uint32_t ob[16];
#pragma unroll
                for (int k = 0; k < 16; k++) ob[k] = bz ? 0u : sm.os[r4 & 1][k * 4 + jq];
                float acc[2][4] = {}, acc2[2][4] = {};
#pragma unroll
                for (int j = 0; j < 4; j++) {
                    if (pass) wait_full(sm, I_WO + j);
#pragma unroll
                    for (int ks = 0; ks < 2; ks++) {
#pragma unroll
                        for (int i = 0; i < 2; i++) {
                            if (i && w == 4) continue;
                            uint32_t a[4];
                            ldsm4t(a, (j ? (j - 1) * 9216 : (I_WO % NST) * SLOT) + ks * 4608 + i * 32 + aoff);
                            mma(ks ? acc2[i] : acc[i], a[0], a[1], a[2], a[3], ob[j * 4 + ks * 2], ob[j * 4 + ks * 2 + 1]);
                        }
                    }
                }
#pragma unroll
                for (int e = 0; e < 4; e++) acc[0][e] = (jq & 2) ? acc[1][e] + acc2[1][e] : acc[0][e] + acc2[0][e];
                f0 = fmaf(g0, acc[0][0], f0);
                f1 = fmaf(g1, acc[0][1], f1);
                const float p0 = fmaf(g0, __shfl_xor_sync(~0u, acc[0][2], 1), f0), p1 = fmaf(g1, __shfl_xor_sync(~0u, acc[0][3], 1), f1);
                float s0 = 0.f, s1 = 0.f, s2 = 0.f, n = 0.f;
                asm volatile("{\n.reg .pred p;\nsetp.ne.u32 p, %8, 0;\n@p atom.relaxed.gpu.global.add.v4.f32 {%0,%1,%2,%3}, [%4], {%5,%6,%7,%7};\n}"
                             : "+f"(s0), "+f"(s1), "+f"(n), "+f"(s2) : "l"(ap), "f"(p0), "f"(p1), "f"(1.f), "r"((uint32_t)(pass && live)) : "memory");
                if (n == (float)(NCTA / 4 - 1)) {
                    out[ec] = __float2bfloat16_rn(s0 + p0);
                    out[ec + D_MODEL] = __float2bfloat16_rn(s1 + p1);
                }
            }
        }
        return;
    }

    const float SC = 0.08838834764831845f * 1.4426950408889634f;
#pragma unroll 1
    for (int pass = 0; pass < npass; pass++) {
        const int nt = pass ? 16 : 1;
        float sc[4][4] = {};
        {
            if (!pass) {
                bar_sync(2, 192);
                asm volatile("barrier.cluster.wait.aligned;" ::: "memory");
            }
            if (pass) {
                wait_msg(sm, 0);
            }
            const float2 qv = sum8<32>(&sm.qin[0][lane]);
            send1(sm, 1, &sm.qs[(c & 3) * 32 + lane], (c & 4) + w, pack_bf16(qv.x, qv.y), pass);
            if (pass) wait_msg(sm, 1);
        }
        {
            uint32_t qf[16];
#pragma unroll
            for (int k = 0; k < 16; k++) qf[k] = sm.qs[(r4 & 1) * 64 + k * 4 + jq];
            const int key = (lane & 7) * 2 + ((chl ^ r4) & 1);
            const uint32_t off = ring + (w * 16 + key) * 128;
            int slot = I_K % NST;
#pragma unroll 1
            for (int tl = 0; tl < nt; tl++) {
                if (pass) wait_full(sm, I_K + tl);
                float s[2][4] = {};
#pragma unroll
                for (int ks = 0; ks < 8; ks++) {
                    uint32_t kf[4];
                    ldsm4(kf, off + slot * SLOT + (ks >> 2) * 8192 + ((((ks & 3) * 2 + (lane >> 4)) ^ (key & 7)) << 4));
                    mma(s[ks & 1], kf[0], kf[1], kf[2], kf[3], qf[2 * ks], qf[2 * ks + 1]);
                }
                release(sm, slot, 5, pass && lane == 0);
                slot = slot == NST - 1 ? 0 : slot + 1;
                if ((tl & 3) == jq) {
#pragma unroll
                    for (int e = 0; e < 4; e++) { sc[0][e] = sc[1][e]; sc[1][e] = sc[2][e]; sc[2][e] = sc[3][e]; sc[3][e] = s[0][e] + s[1][e]; }
                }
            }
        }
        {
            float m0 = -INFINITY, m1 = -INFINITY;
#pragma unroll
            for (int i = 0; i < 4; i++) { m0 = fmaxf(m0, fmaxf(sc[i][0], sc[i][2])); m1 = fmaxf(m1, fmaxf(sc[i][1], sc[i][3])); }
#pragma unroll
            for (int o = 16; o; o >>= 1) { m0 = fmaxf(m0, __shfl_xor_sync(~0u, m0, o)); m1 = fmaxf(m1, __shfl_xor_sync(~0u, m1, o)); }
            sm.mx[w] = make_float2(m0, m1);
            bar_sync(3, 128);
            m0 = fmaxf(fmaxf(sm.mx[0].x, sm.mx[1].x), fmaxf(sm.mx[2].x, sm.mx[3].x));
            m1 = fmaxf(fmaxf(sm.mx[0].y, sm.mx[1].y), fmaxf(sm.mx[2].y, sm.mx[3].y));
            const float ms0 = m0 * SC, ms1 = m1 * SC;
            float l0 = 0.f, l1 = 0.f;
            uint32_t* pd = reinterpret_cast<uint32_t*>(sm.p[jq * 8 + (r4 & 3)]) + w * 2 + (r4 >> 2);
#pragma unroll
            for (int i = 0; i < 4; i++) {
                const uint32_t p0 = pack_bf16(ex2(fmaf(sc[i][0], SC, -ms0)), ex2(fmaf(sc[i][2], SC, -ms0)));
                const uint32_t p1 = pack_bf16(ex2(fmaf(sc[i][1], SC, -ms1)), ex2(fmaf(sc[i][3], SC, -ms1)));
                l0 += bf_lo(p0) + bf_hi(p0);
                l1 += bf_lo(p1) + bf_hi(p1);
                pd[i * 256] = __funnelshift_l(p0, p0, lane & 16);
                pd[i * 256 + 32] = __funnelshift_l(p1, p1, lane & 16);
            }
#pragma unroll
            for (int o = 16; o; o >>= 1) { l0 += __shfl_xor_sync(~0u, l0, o); l1 += __shfl_xor_sync(~0u, l1, o); }
            sm.ls[w] = make_float2(l0, l1);
            bar_sync(3, 128);
            l0 = (sm.ls[0].x + sm.ls[1].x) + (sm.ls[2].x + sm.ls[3].x);
            l1 = (sm.ls[0].y + sm.ls[1].y) + (sm.ls[2].y + sm.ls[3].y);
            send2(sm, 4, reinterpret_cast<float2*>(&sm.oin[c & 3][16]) + lane, (c & 4) + w, lane ? m1 : m0, lane ? l1 : l0, pass && lane < 2);
        }
        {
            float o[2][2][4] = {};
            const uint32_t off = ring + (w >> 1) * 8192 + rowl * 128;
            int slot = I_V % NST;
#pragma unroll 1
            for (int tl = 0; tl < nt; tl++) {
                const uint4 pa = sm.p[tl * 8 + (lane & 7)][0], pb = sm.p[tl * 8 + (lane & 7)][1];
                const uint32_t pf[8] = {pa.x, pa.y, pa.z, pa.w, pb.x, pb.y, pb.z, pb.w};
                if (pass) wait_full(sm, I_V + tl);
#pragma unroll
                for (int ks = 0; ks < 4; ks++) {
#pragma unroll
                    for (int mt = 0; mt < 2; mt++) {
                        uint32_t vf[4];
                        ldsm4t(vf, off + slot * SLOT + ks * 2048 + ((((w & 1) * 4 + mt * 2 + chl) ^ (lane & 7)) << 4));
                        mma(o[mt][ks & 1], vf[0], vf[1], vf[2], vf[3], pf[2 * ks], pf[2 * ks + 1]);
                    }
                }
                release(sm, slot, 5, pass && lane == 0);
                slot = slot == NST - 1 ? 0 : slot + 1;
            }
            float v[4];
#pragma unroll
            for (int e = 0; e < 4; e++) v[e] = (jq & 2) ? o[1][0][e] + o[1][1][e] : o[0][0][e] + o[0][1][e];
            send2(sm, 4, reinterpret_cast<float2*>(sm.oin[c & 3]) + jq * 8 + r4, (c & 4) + w, (jq & 1) ? v[2] : v[0], (jq & 1) ? v[3] : v[1], pass);
        }
        {
            if (pass) wait_msg(sm, 4);
            const int h = lane & 1;
            float2 ml[4];
            float4 v[4];
#pragma unroll
            for (int k = 0; k < 4; k++) { ml[k] = reinterpret_cast<const float2*>(&sm.oin[k][16])[h]; v[k] = sm.oin[k][lane >> 1]; }
            const float M = fmaxf(fmaxf(ml[0].x, ml[1].x), fmaxf(ml[2].x, ml[3].x));
            float L = 0.f, o0 = 0.f, o1 = 0.f;
#pragma unroll
            for (int k = 0; k < 4; k++) {
                const float f = ex2((ml[k].x - M) * SC);
                L = fmaf(f, ml[k].y, L);
                o0 = fmaf(f, h ? v[k].y : v[k].x, o0);
                o1 = fmaf(f, h ? v[k].w : v[k].z, o1);
            }
            const float inv = rcp(L);
            send1(sm, 5, &sm.os[(c >> 2) & 1][(c & 3) * 16 + (lane >> 1)], h * 4 + w, pack_bf16(o0 * inv, o1 * inv), pass);
        }
    }
}

typedef CUresult (*EncFn)(CUtensorMap*, CUtensorMapDataType, cuuint32_t, void*, const cuuint64_t*, const cuuint64_t*,
                          const cuuint32_t*, const cuuint32_t*, CUtensorMapInterleave, CUtensorMapSwizzle,
                          CUtensorMapL2promotion, CUtensorMapFloatOOBfill);

}

extern "C" void kernel_launch(void* const* d_in, const int* in_sizes, int n_in, void* d_out, int out_size) {
    (void)in_sizes; (void)n_in; (void)out_size;
    EncFn enc = nullptr;
    cudaDriverEntryPointQueryResult qr;
    cudaGetDriverEntryPoint("cuTensorMapEncodeTiled", (void**)&enc, cudaEnableDefault, &qr);
    Maps maps;
    const CUtensorMapL2promotion pr = CU_TENSOR_MAP_L2_PROMOTION_L2_256B;
    auto mk = [&](int i, void* p, uint64_t d0, uint64_t d1, uint64_t d2, uint64_t s1, uint64_t s2, uint32_t b0, uint32_t b1, uint32_t b2,
                  CUtensorMapSwizzle sw) {
        cuuint64_t d[3] = {d0, d1, d2}, s[2] = {s1, s2};
        cuuint32_t b[3] = {b0, b1, b2}, e[3] = {1, 1, 1};
        enc(&maps.m[i], CU_TENSOR_MAP_DATA_TYPE_BFLOAT16, 3, p, d, s, b, e, CU_TENSOR_MAP_INTERLEAVE_NONE, sw, pr,
            CU_TENSOR_MAP_FLOAT_OOB_FILL_NONE);
    };
    mk(0, d_in[3], 64, 576, 64, 8192, 128, 64, 24, 4, CU_TENSOR_MAP_SWIZZLE_128B);
    mk(1, d_in[1], 64, 32ull * SK, 2, 256, 128, 64, 64, 2, CU_TENSOR_MAP_SWIZZLE_128B);
    mk(2, d_in[2], 64, 32ull * SK, 2, 256, 128, 64, 64, 2, CU_TENSOR_MAP_SWIZZLE_128B);
    mk(3, d_in[6], 32, 576, 144, 9216, 64, 32, 24, 9, CU_TENSOR_MAP_SWIZZLE_64B);
    mk(4, d_in[8], 576, 4608, 1, 1152, 1152 * 4608, 144, 48, 1, CU_TENSOR_MAP_SWIZZLE_NONE);
    mk(5, d_in[4], 576, 4096, 1, 1152, 1152 * 4096, 144, 32, 1, CU_TENSOR_MAP_SWIZZLE_NONE);
    const int smem = SM_HEAD + NST * SLOT;
    cudaFuncSetAttribute(fused_kernel, cudaFuncAttributeMaxDynamicSharedMemorySize, smem);
    cudaFuncSetAttribute(fused_kernel, cudaFuncAttributePreferredSharedMemoryCarveout, cudaSharedmemCarveoutMaxShared);
    void* scr = nullptr;
    cudaGetSymbolAddress(&scr, g_scr);
    fused_kernel<<<NCTA, NTHR, smem, cudaStreamPerThread>>>(
        (const char*)d_in[3], (const __nv_bfloat16*)d_in[0], (const __nv_bfloat16*)d_in[7], (const __nv_bfloat16*)d_in[9],
        (const __nv_bfloat16*)d_in[10], (__nv_bfloat16*)d_out, (Scratch*)scr, maps);
}
```

```cpp
#include <cuda_runtime.h>
#include <cuda_bf16.h>
#include <cuda.h>
#include <stdint.h>

namespace {

constexpr int D_MODEL = 576;
constexpr int SK = 32768;
constexpr int WIN = 4096;
constexpr int NCTA = 128;
constexpr int SLOT = 16384;
constexpr int NST = 6;
constexpr int INFL = 4;
constexpr int LO = 3, HI = 5, HIT = 7;
constexpr int PACE = 21509;
constexpr int LEAD = 1936;
constexpr int I_K = 3, I_W1 = 19, I_V = 22, I_W2 = 38, I_WO = 41, NITEM = 45;
constexpr int NTHR = 320;
constexpr int SM_HEAD = 17408;
constexpr int SPIN_LIMIT = 1 << 17;

struct Scratch {
    float acc[144 * 64];
    unsigned ready, pad[3];
};
__device__ __align__(1024) Scratch g_scr;

struct __align__(16) Smem {
    uint4 tab[NITEM][2];
    uint2 tab2[NITEM + 1];
    uint64_t full[NITEM];
    uint64_t empty[NST];
    uint64_t go[3], hm;
    uint64_t xb[6];
    float2 g;
    uint4 p[128][2];
    float2 qin[8][32];
    float2 hin[8][36];
    float4 oin[4][17];
    float2 mx[4], ls[4];
    uint32_t qs[128];
    uint32_t hs[2][72];
    uint32_t os[2][68];
};
static_assert(sizeof(Smem) <= SM_HEAD, "");

__device__ __forceinline__ uint32_t s2u(const void* p) { return (uint32_t)__cvta_generic_to_shared(p); }
__device__ __forceinline__ void mbar_init(uint32_t a, int c) { asm volatile("mbarrier.init.shared.b64 [%0], %1;" ::"r"(a), "r"(c) : "memory"); }
__device__ __forceinline__ void mbar_expect(uint32_t a, uint32_t b) { asm volatile("mbarrier.arrive.expect_tx.shared.b64 _, [%0], %1;" ::"r"(a), "r"(b) : "memory"); }
__device__ __forceinline__ void mbar_wait(uint32_t a, uint32_t ph) {
    uint32_t ok;
    int it = 0;
    do {
        asm volatile("{\n.reg .pred p;\nmbarrier.try_wait.parity.shared.b64 p, [%1], %2;\nselp.u32 %0, 1, 0, p;\n}" : "=r"(ok) : "r"(a), "r"(ph) : "memory");
    } while (!ok && ++it < SPIN_LIMIT);
}
__device__ __forceinline__ void mbar_spin(uint32_t a, uint32_t ph) {
    uint32_t ok;
    int it = 0;
    do {
        asm volatile("{\n.reg .pred p;\nmbarrier.test_wait.parity.shared.b64 p, [%1], %2;\nselp.u32 %0, 1, 0, p;\n}" : "=r"(ok) : "r"(a), "r"(ph) : "memory");
    } while (!ok && ++it < SPIN_LIMIT * 64);
}
__device__ __forceinline__ void wait_msg(Smem& sm, int i, uint32_t ph) {
    uint32_t ok;
    int it = 0;
    do {
        asm volatile("{\n.reg .pred p;\nmbarrier.try_wait.parity.acquire.cluster.shared::cta.b64 p, [%1], %2;\nselp.u32 %0, 1, 0, p;\n}"
                     : "=r"(ok) : "r"(s2u(&sm.xb[i])), "r"(ph) : "memory");
    } while (!ok && ++it < SPIN_LIMIT);
}
__device__ __forceinline__ void send1(Smem& sm, int i, const void* dst, int rank, uint32_t v, uint32_t pred) {
    asm volatile("{\n.reg .pred p;\n.reg .b32 a, b;\nsetp.ne.u32 p, %4, 0;\nmapa.shared::cluster.u32 a, %0, %2;\nmapa.shared::cluster.u32 b, %1, %2;\n"
                 "@p st.async.shared::cluster.mbarrier::complete_tx::bytes.u32 [a], %3, [b];\n}"
                 ::"r"(s2u(dst)), "r"(s2u(&sm.xb[i])), "r"(rank), "r"(v), "r"(pred) : "memory");
}
__device__ __forceinline__ void send2(Smem& sm, int i, const void* dst, int rank, float v0, float v1, uint32_t pred) {
    asm volatile("{\n.reg .pred p;\n.reg .b32 a, b;\nsetp.ne.u32 p, %5, 0;\nmapa.shared::cluster.u32 a, %0, %2;\nmapa.shared::cluster.u32 b, %1, %2;\n"
                 "@p st.async.shared::cluster.mbarrier::complete_tx::bytes.v2.f32 [a], {%3, %4}, [b];\n}"
                 ::"r"(s2u(dst)), "r"(s2u(&sm.xb[i])), "r"(rank), "f"(v0), "f"(v1), "r"(pred) : "memory");
}
__device__ __forceinline__ void scatter(Smem& sm, int i, const void* dst, int j, const float* v, int lane, uint32_t pred) {
    const bool odd = lane & 4;
    const float y0 = __shfl_xor_sync(~0u, odd ? v[0] : v[2], 4), y1 = __shfl_xor_sync(~0u, odd ? v[1] : v[3], 4);
    send2(sm, i, dst, j, odd ? y0 : v[0], odd ? v[2] : y0, pred);
    send2(sm, i, dst, j + 4, odd ? y1 : v[1], odd ? v[3] : y1, pred);
}
template <int P> __device__ __forceinline__ float2 sum8(const float2* p) {
    float2 v[8];
#pragma unroll
    for (int k = 0; k < 8; k++) v[k] = p[k * P];
    return make_float2(((v[0].x + v[1].x) + (v[2].x + v[3].x)) + ((v[4].x + v[5].x) + (v[6].x + v[7].x)),
                       ((v[0].y + v[1].y) + (v[2].y + v[3].y)) + ((v[4].y + v[5].y) + (v[6].y + v[7].y)));
}
__device__ __forceinline__ void tma3d_ef(uint32_t dst, const CUtensorMap* m, int c0, int c1, int c2, uint32_t bar, uint64_t pol) {
    asm volatile("cp.async.bulk.tensor.3d.shared::cluster.global.mbarrier::complete_tx::bytes.L2::cache_hint [%0], [%1, {%3, %4, %5}], [%2], %6;"
                 ::"r"(dst), "l"(m), "r"(bar), "r"(c0), "r"(c1), "r"(c2), "l"(pol) : "memory");
}
__device__ __forceinline__ void ldsm4(uint32_t* r, uint32_t a) {
    asm volatile("ldmatrix.sync.aligned.m8n8.x4.shared.b16 {%0,%1,%2,%3}, [%4];" : "=r"(r[0]), "=r"(r[1]), "=r"(r[2]), "=r"(r[3]) : "r"(a) : "memory");
}
__device__ __forceinline__ void ldsm4t(uint32_t* r, uint32_t a) {
    asm volatile("ldmatrix.sync.aligned.m8n8.x4.trans.shared.b16 {%0,%1,%2,%3}, [%4];" : "=r"(r[0]), "=r"(r[1]), "=r"(r[2]), "=r"(r[3]) : "r"(a) : "memory");
}
__device__ __forceinline__ void mma(float* c, uint32_t a0, uint32_t a1, uint32_t a2, uint32_t a3, uint32_t b0, uint32_t b1) {
    asm volatile("mma.sync.aligned.m16n8k16.row.col.f32.bf16.bf16.f32 {%0,%1,%2,%3}, {%4,%5,%6,%7}, {%8,%9}, {%0,%1,%2,%3};"
                 : "+f"(c[0]), "+f"(c[1]), "+f"(c[2]), "+f"(c[3]) : "r"(a0), "r"(a1), "r"(a2), "r"(a3), "r"(b0), "r"(b1));
}
__device__ __forceinline__ uint32_t pack_bf16(float lo, float hi) {
    uint32_t r;
    asm("cvt.rn.bf16x2.f32 %0, %1, %2;" : "=r"(r) : "f"(hi), "f"(lo));
    return r;
}
__device__ __forceinline__ float bf_lo(uint32_t v) { return __uint_as_float(v << 16); }
__device__ __forceinline__ float bf_hi(uint32_t v) { return __uint_as_float(v & 0xffff0000u); }
__device__ __forceinline__ float ex2(float v) { float r; asm("ex2.approx.ftz.f32 %0, %1;" : "=f"(r) : "f"(v)); return r; }
__device__ __forceinline__ float rcp(float v) { float r; asm("rcp.approx.ftz.f32 %0, %1;" : "=f"(r) : "f"(v)); return r; }
__device__ __forceinline__ void bar_sync(int id, int n) { asm volatile("bar.sync %0, %1;" ::"r"(id), "r"(n) : "memory"); }
__device__ __forceinline__ void wait_full(Smem& sm, int i, uint32_t ph) { mbar_wait(s2u(&sm.full[i]), ph); }
__device__ __forceinline__ void release(Smem& sm, int slot, int n, uint32_t pred) {
    __syncwarp();
    asm volatile("{\n.reg .pred p;\nsetp.ne.u32 p, %2, 0;\n@p mbarrier.arrive.shared.b64 _, [%0], %1;\n}" ::"r"(s2u(&sm.empty[slot])), "r"(n), "r"(pred) : "memory");
}

__device__ __forceinline__ uint32_t ldg32(const void* p) {
    uint32_t v;
    asm volatile("ld.global.nc.u32 %0, [%1];" : "=r"(v) : "l"(p));
    return v;
}

struct Maps { CUtensorMap m[5]; };

__global__ void __cluster_dims__(8, 1, 1) __launch_bounds__(NTHR, 2)
fused_kernel(const char* __restrict__ wq, const char* __restrict__ w2, const __nv_bfloat16* __restrict__ x, const __nv_bfloat16* __restrict__ b1,
             const __nv_bfloat16* __restrict__ b2, const __nv_bfloat16* __restrict__ gate_w,
             __nv_bfloat16* __restrict__ out, Scratch* __restrict__ scr, const __grid_constant__ Maps maps) {
    extern __shared__ __align__(1024) unsigned char smem_raw[];
    Smem& sm = *reinterpret_cast<Smem*>(smem_raw);
    asm volatile("{\n.reg .pred p;\n.reg .b32 t;\n.reg .b64 a;\nmov.u32 t, %%ctaid.x;\nmad.wide.u32 a, t, 36864, %0;\n"
                 "mov.u32 t, %%tid.x;\nsetp.eq.u32 p, t, 0;\n@p cp.async.bulk.prefetch.L2.global [a], 36864;\n}" ::"l"(wq) : "memory");
    const uint32_t ring = s2u(smem_raw) + SM_HEAD;
    const int tid = threadIdx.x, lane = tid & 31;
    const int c = blockIdx.x;
    const int warp = __shfl_sync(~0u, tid >> 5, 0);

    if (tid == 0) {
#pragma unroll
        for (int i = 0; i < 5; i++) asm volatile("prefetch.tensormap [%0];" ::"l"(&maps.m[i]) : "memory");
#pragma unroll
        for (int i = 0; i < NST; i++) mbar_init(s2u(&sm.full[i]), 1);
#pragma unroll
        for (int i = 0; i < NST; i++) mbar_init(s2u(&sm.empty[i]), 20);
        asm volatile("fence.proxy.async.shared::cta;" ::: "memory");
    }
    if (tid < NITEM) {
        const int i = tid;
        const uint32_t bars = s2u(sm.full);
        const bool q = i < 3, w1 = i >= I_W1 && i < I_W1 + 3, wo = i >= I_WO, w2o = i >= I_W2, kv = !(q || w1 || w2o), v = i >= I_V;
        const int k = i - (q ? 0 : w1 ? I_W1 : wo ? I_WO : w2o ? I_W2 : v ? I_V : I_K);
        const int kvrow = ((((c >> 2) & 1) * 16 + (c >> 3)) * SK) + (SK - WIN) + (c & 3) * 64;
        const uint32_t c0 = wo ? (c & 3) * 144 : 0, c2 = (c >> 3) * (q ? 4 : w1 ? 9 : 0);
        const uint32_t c1 = k * (kv ? 256 : wo ? 32 : 192) + (kv ? kvrow : wo ? (c >> 2) * 128 : (c & 7) * 24);
        const uint32_t bytes = kv ? 16384 : q ? 12288 : wo ? 9216 : 13824;
        const uint32_t map = q ? 0 : w1 ? 3 : wo ? 4 : w2o ? 8 : v ? 2 : 1;
        const int j = i - (i > I_WO ? HIT : HI);
        const int j2 = i < INFL ? -1 : i - LO;
        const int cum = (q ? 0 : w1 ? 72 + (I_W1 - 3) * 32 : wo ? 72 + 1024 + 162 : w2o ? 72 + 1024 + 81 : v ? 72 + 512 + (I_V - 19) * 27 : 72 + (I_K - 3) * 27) * 512 + (k + 1) * bytes;
        uint32_t now;
        asm volatile("mov.u32 %0, %%globaltimer_lo;" : "=r"(now));
        const int lap = (i * 43) >> 8, slot = i - lap * NST;
        const uint32_t fl = (j < 0) | ((~lap & 1) << 1) | ((j2 < 0) << 2) | (map << 10);
        sm.tab[i][0] = make_uint4(ring + slot * (i > I_WO ? 9216 : SLOT), bars + (map == 8 ? NITEM + NST + k : i) * 8, c0, c1);
        sm.tab[i][1] = make_uint4(c2, bytes, bars + (j < 0 ? i : j) * 8, fl | ((bars + (NITEM + slot - (i == NITEM - 1)) * 8) << 16));
        sm.tab2[i] = make_uint2(bars + (j2 < 0 ? i : j2) * 8, now + (((cum >> 9) * PACE) >> 10) - LEAD);
    }
    int warp2;
    asm volatile("mov.u32 %0, %1;" : "=r"(warp2) : "r"(warp));
    if (warp2 == 0) {
        asm volatile("bar.arrive 0, %0;" ::"n"(NTHR - 128) : "memory");
        asm volatile("bar.arrive 2, 192;" ::: "memory");
        __syncwarp();
        if (lane != 0) return;
        {
            uint64_t pol;
            asm volatile("createpolicy.fractional.L2::evict_first.b64 %0, 1.0;" : "=l"(pol));
#pragma unroll 1
            for (int i = 0; i < NITEM; i++) {
                const uint4 a = sm.tab[i][0], b = sm.tab[i][1];
                const char* map = reinterpret_cast<const char*>(&maps) + ((b.w >> 3) & 0x380);
                asm volatile("" : "+l"(map));
                mbar_wait((b.w >> 16) | (a.y & 0xff000000u), (b.w >> 1) & 1);
                mbar_expect(a.y, b.y);
                mbar_wait(b.z, b.w & 1);
                {
                    const uint2 d = sm.tab2[i];
                    uint32_t go;
                    int it = 0;
                    do {
                        asm volatile("{\n.reg .pred p;\n.reg .b32 t;\nmov.u32 t, %%globaltimer_lo;\nmbarrier.test_wait.parity.shared.b64 p, [%1], %2;\n"
                                     "sub.s32 t, t, %3;\nsetp.ge.or.s32 p, t, 0, p;\nselp.u32 %0, 1, 0, p;\n}"
                                     : "=r"(go) : "r"(d.x), "r"((b.w >> 2) & 1), "r"(d.y) : "memory");
                    } while (!go && ++it < SPIN_LIMIT);
                }
                if (b.w & (8 << 10)) asm volatile("mbarrier.complete_tx.relaxed.cta.shared::cta.b64 [%0], %1;" ::"r"(a.y), "r"(b.y) : "memory");
                else tma3d_ef(a.x, reinterpret_cast<const CUtensorMap*>(map), a.z, a.w, b.x, a.y, pol);
                if (i == I_W2 - 1) mbar_wait(s2u(&sm.hm), 0);
                if (i == INFL - 1) asm volatile("barrier.cluster.arrive.relaxed;" ::: "memory");
            }
        }
    }
    if (warp == 0) return;

    const int t = tid - (warp > 4 ? 160 : 32), w = warp - (warp > 4 ? 5 : 1);
    const int rowl = ((lane >> 4) << 3) + (lane & 7);
    const int chl = (lane >> 3) & 1;
    const int r4 = lane >> 2, jq = lane & 3;
    int npass;
    asm volatile("mov.u32 %0, 2;" : "=r"(npass));
    if (tid == 319) {
#pragma unroll
        for (int i = 0; i < 6; i++) mbar_init(s2u(&sm.xb[i]), 1);
        asm volatile("fence.mbarrier_init.release.cluster;" ::: "memory");
    }
    __syncwarp();
    asm volatile("barrier.cluster.arrive.relaxed.aligned;" ::: "memory");

    if (warp > 4) {
        const int hd = (t * 57) >> 11, hi = t - hd * 36;
        const int pr = jq * 8 + (r4 & 1) * 4 + (r4 >> 1);
        uint32_t xf[9], epoch = 0;
#pragma unroll
        for (int k = 0; k < 9; k++) xf[k] = ldg32(x + (r4 & 1) * D_MODEL + (c & 7) * 24 + (k / 3) * 192 + (k % 3) * 8 + jq * 2);
        const uint32_t bias = ldg32(b1 + (c >> 3) * 288 + (c & 3) * 72 + hi * 2);
        if (w == 4) {
            if (lane == 31) {
                asm volatile("ld.relaxed.gpu.global.u32 %0, [%1];" : "=r"(epoch) : "l"(&scr->ready));
                mbar_expect(s2u(&sm.xb[0]), 2048);
                mbar_expect(s2u(&sm.xb[1]), 512);
                mbar_expect(s2u(&sm.xb[2]), 2304);
                mbar_expect(s2u(&sm.xb[3]), 576);
                mbar_expect(s2u(&sm.xb[4]), 1088);
                mbar_expect(s2u(&sm.xb[5]), 512);
#pragma unroll 1
                for (int i = NST; i < NITEM; i++) mbar_init(s2u(&sm.full[i]), i >= I_W2 && i < I_WO ? 160 : 1);
#pragma unroll
                for (int i = 0; i < 3; i++) mbar_init(s2u(&sm.go[i]), 1);
                mbar_init(s2u(&sm.hm), 1);
                asm volatile("fence.proxy.async.shared::cta;" ::: "memory");
            }
            __syncwarp();
            asm volatile("bar.arrive 2, 192;" ::: "memory");
        }
        bar_sync(0, NTHR - 128);
        asm volatile("barrier.cluster.wait.aligned;" ::: "memory");
        if (w == 4) {
            float s0 = 0.f, s1 = 0.f;
            uint32_t bv[3];
#pragma unroll
            for (int i = 0; i < 3; i++) bv[i] = ldg32(b2 + (c & 3) * 144 + i * 48 + (lane < 24 ? lane * 2 : 0));
#pragma unroll
            for (int i = 0; i < 9; i++) {
                const uint32_t gv = ldg32(gate_w + i * 64 + lane * 2), a = ldg32(x + i * 64 + lane * 2), b = ldg32(x + D_MODEL + i * 64 + lane * 2);
                s0 = fmaf(bf_lo(gv), bf_lo(a), fmaf(bf_hi(gv), bf_hi(a), s0));
                s1 = fmaf(bf_lo(gv), bf_lo(b), fmaf(bf_hi(gv), bf_hi(b), s1));
            }
#pragma unroll
            for (int o = 16; o; o >>= 1) { s0 += __shfl_xor_sync(~0u, s0, o); s1 += __shfl_xor_sync(~0u, s1, o); }
            s0 = 1.f / (1.f + __expf(-s0));
            s1 = 1.f / (1.f + __expf(-s1));
            sm.g = make_float2(s0, s1);
            asm volatile("bar.arrive 4, 160;" ::: "memory");
            if (c < 4) {
#pragma unroll
                for (int i = 0; i < 3; i++) {
                    float* ip = scr->acc + (c * 36 + i * 12 + (lane >> 1)) * 64 + (lane & 1) * 8;
                    if (lane < 24) {
                        asm volatile("st.relaxed.gpu.global.v4.f32 [%0], {%1,%2,%3,%3};" ::"l"(ip), "f"((1.f - s0) * bf_lo(bv[i])), "f"((1.f - s1) * bf_lo(bv[i])), "f"(0.f) : "memory");
                        asm volatile("st.relaxed.gpu.global.v4.f32 [%0], {%1,%2,%3,%3};" ::"l"(ip + 4), "f"((1.f - s0) * bf_hi(bv[i])), "f"((1.f - s1) * bf_hi(bv[i])), "f"(0.f) : "memory");
                    }
                }
                __syncwarp();
                asm volatile("fence.acq_rel.gpu;" ::: "memory");
            }
            if (lane == 31) asm volatile("red.relaxed.gpu.global.add.u32 [%0], 1;" ::"l"(&scr->ready) : "memory");
        }
        if (w < 4) {
            float acc[4][4] = {};
#pragma unroll
            for (int j = 0; j < 3; j++) {
                wait_full(sm, j, 0);
#pragma unroll
                for (int mt = 0; mt < 4; mt++) {
#pragma unroll
                    for (int ks = 0; ks < 2; ks++) {
                        const int r = ks ? 16 + (lane & 7) : rowl;
                        uint32_t a[4];
                        ldsm4t(a, ring + j * SLOT + w * 3072 + r * 128 + (((mt * 2 + chl) ^ (r & 7)) << 4));
                        mma(acc[mt], a[0], a[1], a[2], a[3], xf[j * 3 + ks * 2], ks ? 0u : xf[j * 3 + 1]);
                    }
                }
                release(sm, j, 5, lane == 0);
            }
            float v[4];
#pragma unroll
            for (int e = 0; e < 4; e++) v[e] = (jq & 2) ? ((jq & 1) ? acc[3][e] : acc[2][e]) : ((jq & 1) ? acc[1][e] : acc[0][e]);
            scatter(sm, 0, &sm.qin[c & 7][pr], w, v, lane, 1);
            bar_sync(4, 160);
        }
        const float g0 = sm.g.x, g1 = sm.g.y;
        const int ec = (c & 3) * 144 + w * 32 + jq * 8 + r4;
        const bool live = w * 4 + jq < 18;
        float* ap = scr->acc + (ec >> 2) * 64 + (r4 & 3) * 4;
#pragma unroll 1
        for (int pass = 0; pass < npass; pass++) {
            const uint32_t dry = pass ^ 1;
            {
                float acc[4][4] = {};
#pragma unroll
                for (int j = 0; j < 3; j++) {
                    wait_full(sm, pass ? I_W1 + j : I_WO, dry);
#pragma unroll
                    for (int mt = 0; mt < 4; mt++) {
                        if (mt > 1 && w == 4) continue;
#pragma unroll
                        for (int ks = 0; ks < 2; ks++) {
                            const int r = ks ? 16 + (lane & 7) : rowl;
                            uint32_t a[4];
                            ldsm4t(a, ring + ((I_W1 + j) % NST) * SLOT + (w * 2 + (mt >> 1)) * 1536 + r * 64 + ((((mt & 1) * 2 + chl) ^ ((r >> 1) & 3)) << 4));
                            mma(acc[mt], a[0], a[1], a[2], a[3], xf[j * 3 + ks * 2], ks ? 0u : xf[j * 3 + 1]);
                        }
                    }
                    release(sm, (I_W1 + j) % NST, 4, pass && lane == 0);
                }
                float v[4];
#pragma unroll
                for (int e = 0; e < 4; e++) v[e] = (jq & 2) ? ((jq & 1) ? acc[3][e] : acc[2][e]) : ((jq & 1) ? acc[1][e] : acc[0][e]);
                const int cp = w * 32 + pr, cj = (cp * 57) >> 11;
                scatter(sm, 2, &sm.hin[c & 7][cp - cj * 36], cj & 3, v, lane, pass && live);
                wait_msg(sm, 2 + 3 * dry, dry);
                const float2 hv = sum8<36>(&sm.hin[0][hi]);
                const uint32_t hr = pack_bf16(hv.x, hv.y), hb = pack_bf16(bf_lo(hr) + bf_lo(bias), bf_hi(hr) + bf_hi(bias));
                const float h0 = fmaxf(bf_lo(hb), 0.f), h1 = fmaxf(bf_hi(hb), 0.f);
                send1(sm, 3, &sm.hs[(c >> 2) & 1][(c & 1) * 36 + hi], (c & 2) * 2 + (hd & 3), pack_bf16(h0 * h0, h1 * h1), pass && t < 144);
                if (pass && t == 159) {
                    uint32_t seen;
                    int it = 0;
                    do {
                        asm volatile("ld.acquire.gpu.global.u32 %0, [%1];" : "=r"(seen) : "l"(&scr->ready) : "memory");
                    } while ((int)(seen - (epoch / NCTA + 1u) * NCTA) < 0 && ++it < SPIN_LIMIT);
                }
                __syncwarp();
                bar_sync(1, 160);
            }
            {
                float f0, f1;
                const uint32_t aoff = ring + rowl * 288 + w * 64 + ((chl ^ (lane >> 2)) & 1) * 16;
                const bool bz = (r4 ^ jq) & 2;
                {
                    wait_msg(sm, 3 + 2 * dry, dry);
                    float acc[2][4] = {};
                    uint32_t hb[18];
#pragma unroll
                    for (int k = 0; k < 18; k++) hb[k] = bz ? 0u : sm.hs[r4 & 1][k * 4 + jq];
                    const uint16_t* hh = reinterpret_cast<const uint16_t*>(sm.hs);
                    uint32_t mk[6];
#pragma unroll
                    for (int k = 0; k < 6; k++) {
                        const int r = (k >> 1) * 48 + ((k & 1) ? 32 + (lane & 15) : lane);
                        mk[k] = __ballot_sync(~0u, (hh[r] | hh[144 + r]) != 0);
                    }
                    if (w == 4 && pass) {
                        const int z0 = 2 * __popc(~mk[0]) + __popc(~mk[1]), z1 = 2 * __popc(~mk[2]) + __popc(~mk[3]), z2 = 2 * __popc(~mk[4]) + __popc(~mk[5]);
                        if (lane < NITEM - I_W2) sm.tab2[I_W2 + lane].y -= ((z0 + (lane > 0 ? z1 : 0) + (lane > 1 ? z2 : 0)) * (144 * PACE >> 8)) >> 11;
                        __syncwarp();
                        if (lane == 0) asm volatile("mbarrier.arrive.shared.b64 _, [%0];" ::"r"(s2u(&sm.hm)) : "memory");
                    }
                    uint64_t pol;
                    asm volatile("createpolicy.fractional.L2::evict_first.b64 %0, 1.0;" : "=l"(pol));
                    const char* src = w2 + (c >> 2) * (144 * 1152) + (c & 3) * 288 + t * 16;
                    const uint32_t dst = __shfl_sync(~0u, ring + t * 16, lane);
#pragma unroll
                    for (int j = 0; j < 3; j++) {
                        mbar_wait(s2u(&sm.go[j]), dry);
#pragma unroll
                        for (int k = 0; k < 6; k++) {
                            const uint32_t r = ((k * 160 + t) * 3641) >> 16;
                            asm volatile("{\n.reg .pred p, z;\nsetp.ne.u32 p, %4, 0;\nsetp.eq.u32 z, %2, 0;\n"
                                         "@p cp.async.cg.shared.global.L2::cache_hint.L2::128B [%0], [%1], 16, z, %3;\n}"
                                         ::"r"(dst + ((I_W2 + j) % NST) * SLOT + k * 2560), "l"(src + r * 864 + (j * 55296 + k * 2560)),
                                         "r"((uint32_t)((mk[2 * j] | (uint64_t)mk[2 * j + 1] << 32) >> r) & 1), "l"(pol),
                                         "r"((uint32_t)(pass && (k < 5 || t < 64))) : "memory");
                        }
                        asm volatile("{\n.reg .pred p;\nsetp.ne.u32 p, %1, 0;\n@p cp.async.mbarrier.arrive.noinc.shared.b64 [%0];\n}"
                                     ::"r"(s2u(&sm.full[I_W2 + j])), "r"(pass) : "memory");
                    }
#pragma unroll
                    for (int j = 0; j < 3; j++) {
                        wait_full(sm, I_W2 + j, dry);
#pragma unroll
                        for (int ks = 0; ks < 3; ks++) {
#pragma unroll
                            for (int i = 0; i < 2; i++) {
                                if (i && w == 4) continue;
                                uint32_t a[4];
                                ldsm4t(a, ((I_W2 + j) % NST) * SLOT + ks * 4608 + i * 32 + aoff);
                                mma(acc[i], a[0], a[1], a[2], a[3], hb[j * 6 + ks * 2], hb[j * 6 + ks * 2 + 1]);
                            }
                        }
                    }
#pragma unroll
                    for (int e = 0; e < 4; e++) acc[0][e] = (jq & 2) ? acc[1][e] : acc[0][e];
                    f0 = (1.f - g0) * (acc[0][0] + __shfl_xor_sync(~0u, acc[0][2], 1));
                    f1 = (1.f - g1) * (acc[0][1] + __shfl_xor_sync(~0u, acc[0][3], 1));
                }
                wait_msg(sm, 5, dry);
                uint32_t ob[16];
#pragma unroll
                for (int k = 0; k < 16; k++) ob[k] = bz ? 0u : sm.os[r4 & 1][k * 4 + jq];
                float acc[2][4] = {}, acc2[2][4] = {};
#pragma unroll
                for (int j = 0; j < 4; j++) {
                    mbar_spin(s2u(&sm.full[I_WO + j]), dry);
#pragma unroll
                    for (int ks = 0; ks < 2; ks++) {
#pragma unroll
                        for (int i = 0; i < 2; i++) {
                            if (i && w == 4) continue;
                            uint32_t a[4];
                            ldsm4t(a, (j ? (j - 1) * 9216 : (I_WO % NST) * SLOT) + ks * 4608 + i * 32 + aoff);
                            mma(ks ? acc2[i] : acc[i], a[0], a[1], a[2], a[3], ob[j * 4 + ks * 2], ob[j * 4 + ks * 2 + 1]);
                        }
                    }
                }
#pragma unroll
                for (int e = 0; e < 4; e++) acc[0][e] = (jq & 2) ? acc[1][e] + acc2[1][e] : acc[0][e] + acc2[0][e];
                f0 = fmaf(g0, acc[0][0], f0);
                f1 = fmaf(g1, acc[0][1], f1);
                const float p0 = fmaf(g0, __shfl_xor_sync(~0u, acc[0][2], 1), f0), p1 = fmaf(g1, __shfl_xor_sync(~0u, acc[0][3], 1), f1);
                float s0 = 0.f, s1 = 0.f, s2 = 0.f, n = 0.f;
                asm volatile("{\n.reg .pred p;\nsetp.ne.u32 p, %8, 0;\n@p atom.relaxed.gpu.global.add.v4.f32 {%0,%1,%2,%3}, [%4], {%5,%6,%7,%7};\n}"
                             : "+f"(s0), "+f"(s1), "+f"(n), "+f"(s2) : "l"(ap), "f"(p0), "f"(p1), "f"(1.f), "r"((uint32_t)(pass && live)) : "memory");
                if (n == (float)(NCTA / 4 - 1)) {
                    out[ec] = __float2bfloat16_rn(s0 + p0);
                    out[ec + D_MODEL] = __float2bfloat16_rn(s1 + p1);
                }
            }
        }
        return;
    }

    const float SC = 0.08838834764831845f * 1.4426950408889634f;
#pragma unroll 1
    for (int pass = 0; pass < npass; pass++) {
        const int nt = pass ? 16 : 1;
        const uint32_t dry = pass ^ 1;
        float sc[4][4] = {};
        {
            if (!pass) {
                bar_sync(2, 192);
                asm volatile("barrier.cluster.wait.aligned;" ::: "memory");
            }
            wait_msg(sm, dry, dry);
            const float2 qv = sum8<32>(&sm.qin[0][lane]);
            send1(sm, 1, &sm.qs[(c & 3) * 32 + lane], (c & 4) + w, pack_bf16(qv.x, qv.y), pass);
            wait_msg(sm, 1, dry);
        }
        {
            uint32_t qf[16];
#pragma unroll
            for (int k = 0; k < 16; k++) qf[k] = sm.qs[(r4 & 1) * 64 + k * 4 + jq];
            const int key = (lane & 7) * 2 + ((chl ^ r4) & 1);
            const uint32_t off = ring + (w * 16 + key) * 128;
            int slot = I_K % NST;
#pragma unroll 1
            for (int tl = 0; tl < nt; tl++) {
                wait_full(sm, (pass ? I_K : I_V) + tl, dry);
                float s[2][4] = {};
#pragma unroll
                for (int ks = 0; ks < 8; ks++) {
                    uint32_t kf[4];
                    ldsm4(kf, off + slot * SLOT + (ks >> 2) * 8192 + ((((ks & 3) * 2 + (lane >> 4)) ^ (key & 7)) << 4));
                    mma(s[ks & 1], kf[0], kf[1], kf[2], kf[3], qf[2 * ks], qf[2 * ks + 1]);
                }
                release(sm, slot, 5, pass && lane == 0);
                slot = slot == NST - 1 ? 0 : slot + 1;
                if ((tl & 3) == jq) {
#pragma unroll
                    for (int e = 0; e < 4; e++) { sc[0][e] = sc[1][e]; sc[1][e] = sc[2][e]; sc[2][e] = sc[3][e]; sc[3][e] = s[0][e] + s[1][e]; }
                }
            }
        }
        {
            float m0 = -INFINITY, m1 = -INFINITY;
#pragma unroll
            for (int i = 0; i < 4; i++) { m0 = fmaxf(m0, fmaxf(sc[i][0], sc[i][2])); m1 = fmaxf(m1, fmaxf(sc[i][1], sc[i][3])); }
#pragma unroll
            for (int o = 16; o; o >>= 1) { m0 = fmaxf(m0, __shfl_xor_sync(~0u, m0, o)); m1 = fmaxf(m1, __shfl_xor_sync(~0u, m1, o)); }
            sm.mx[w] = make_float2(m0, m1);
            bar_sync(3, 128);
            m0 = fmaxf(fmaxf(sm.mx[0].x, sm.mx[1].x), fmaxf(sm.mx[2].x, sm.mx[3].x));
            m1 = fmaxf(fmaxf(sm.mx[0].y, sm.mx[1].y), fmaxf(sm.mx[2].y, sm.mx[3].y));
            const float ms0 = m0 * SC, ms1 = m1 * SC;
            float l0 = 0.f, l1 = 0.f;
            uint32_t* pd = reinterpret_cast<uint32_t*>(sm.p[jq * 8 + (r4 & 3)]) + w * 2 + (r4 >> 2);
#pragma unroll
            for (int i = 0; i < 4; i++) {
                const uint32_t p0 = pack_bf16(ex2(fmaf(sc[i][0], SC, -ms0)), ex2(fmaf(sc[i][2], SC, -ms0)));
                const uint32_t p1 = pack_bf16(ex2(fmaf(sc[i][1], SC, -ms1)), ex2(fmaf(sc[i][3], SC, -ms1)));
                l0 += bf_lo(p0) + bf_hi(p0);
                l1 += bf_lo(p1) + bf_hi(p1);
                pd[i * 256] = __funnelshift_l(p0, p0, lane & 16);
                pd[i * 256 + 32] = __funnelshift_l(p1, p1, lane & 16);
            }
#pragma unroll
            for (int o = 16; o; o >>= 1) { l0 += __shfl_xor_sync(~0u, l0, o); l1 += __shfl_xor_sync(~0u, l1, o); }
            sm.ls[w] = make_float2(l0, l1);
            bar_sync(3, 128);
            l0 = (sm.ls[0].x + sm.ls[1].x) + (sm.ls[2].x + sm.ls[3].x);
            l1 = (sm.ls[0].y + sm.ls[1].y) + (sm.ls[2].y + sm.ls[3].y);
            send2(sm, 4, reinterpret_cast<float2*>(&sm.oin[c & 3][16]) + lane, (c & 4) + w, lane ? m1 : m0, lane ? l1 : l0, pass && lane < 2);
        }
        {
            float o[2][2][4] = {};
            const uint32_t off = ring + (w >> 1) * 8192 + rowl * 128;
            int slot = I_V % NST;
#pragma unroll 1
            for (int tl = 0; tl < nt; tl++) {
                const uint4 pa = sm.p[tl * 8 + (lane & 7)][0], pb = sm.p[tl * 8 + (lane & 7)][1];
                const uint32_t pf[8] = {pa.x, pa.y, pa.z, pa.w, pb.x, pb.y, pb.z, pb.w};
                wait_full(sm, I_V + tl, dry);
#pragma unroll
                for (int ks = 0; ks < 4; ks++) {
#pragma unroll
                    for (int mt = 0; mt < 2; mt++) {
                        uint32_t vf[4];
                        ldsm4t(vf, off + slot * SLOT + ks * 2048 + ((((w & 1) * 4 + mt * 2 + chl) ^ (lane & 7)) << 4));
                        mma(o[mt][ks & 1], vf[0], vf[1], vf[2], vf[3], pf[2 * ks], pf[2 * ks + 1]);
                    }
                }
                release(sm, slot, 5, pass && lane == 0);
                slot = slot == NST - 1 ? 0 : slot + 1;
            }
            float v[4];
#pragma unroll
            for (int e = 0; e < 4; e++) v[e] = (jq & 2) ? o[1][0][e] + o[1][1][e] : o[0][0][e] + o[0][1][e];
            send2(sm, 4, reinterpret_cast<float2*>(sm.oin[c & 3]) + jq * 8 + r4, (c & 4) + w, (jq & 1) ? v[2] : v[0], (jq & 1) ? v[3] : v[1], pass);
        }
        {
            wait_msg(sm, 4, dry);
            const int h = lane & 1;
            float2 ml[4];
            float4 v[4];
#pragma unroll
            for (int k = 0; k < 4; k++) { ml[k] = reinterpret_cast<const float2*>(&sm.oin[k][16])[h]; v[k] = sm.oin[k][lane >> 1]; }
            const float M = fmaxf(fmaxf(ml[0].x, ml[1].x), fmaxf(ml[2].x, ml[3].x));
            float L = 0.f, o0 = 0.f, o1 = 0.f;
#pragma unroll
            for (int k = 0; k < 4; k++) {
                const float f = ex2((ml[k].x - M) * SC);
                L = fmaf(f, ml[k].y, L);
                o0 = fmaf(f, h ? v[k].y : v[k].x, o0);
                o1 = fmaf(f, h ? v[k].w : v[k].z, o1);
            }
            const float inv = rcp(L);
            send1(sm, 5, &sm.os[(c >> 2) & 1][(c & 3) * 16 + (lane >> 1)], h * 4 + w, pack_bf16(o0 * inv, o1 * inv), pass);
        }
    }
}

typedef CUresult (*EncFn)(CUtensorMap*, CUtensorMapDataType, cuuint32_t, void*, const cuuint64_t*, const cuuint64_t*,
                          const cuuint32_t*, const cuuint32_t*, CUtensorMapInterleave, CUtensorMapSwizzle,
                          CUtensorMapL2promotion, CUtensorMapFloatOOBfill);

}

extern "C" void kernel_launch(void* const* d_in, const int* in_sizes, int n_in, void* d_out, int out_size) {
    (void)in_sizes; (void)n_in; (void)out_size;
    EncFn enc = nullptr;
    cudaDriverEntryPointQueryResult qr;
    cudaGetDriverEntryPoint("cuTensorMapEncodeTiled", (void**)&enc, cudaEnableDefault, &qr);
    Maps maps;
    const CUtensorMapL2promotion pr = CU_TENSOR_MAP_L2_PROMOTION_L2_256B;
    auto mk = [&](int i, void* p, uint64_t d0, uint64_t d1, uint64_t d2, uint64_t s1, uint64_t s2, uint32_t b0, uint32_t b1, uint32_t b2,
                  CUtensorMapSwizzle sw) {
        cuuint64_t d[3] = {d0, d1, d2}, s[2] = {s1, s2};
        cuuint32_t b[3] = {b0, b1, b2}, e[3] = {1, 1, 1};
        enc(&maps.m[i], CU_TENSOR_MAP_DATA_TYPE_BFLOAT16, 3, p, d, s, b, e, CU_TENSOR_MAP_INTERLEAVE_NONE, sw, pr,
            CU_TENSOR_MAP_FLOAT_OOB_FILL_NONE);
    };
    mk(0, d_in[3], 64, 576, 64, 8192, 128, 64, 24, 4, CU_TENSOR_MAP_SWIZZLE_128B);
    mk(1, d_in[1], 64, 32ull * SK, 2, 256, 128, 64, 64, 2, CU_TENSOR_MAP_SWIZZLE_128B);
    mk(2, d_in[2], 64, 32ull * SK, 2, 256, 128, 64, 64, 2, CU_TENSOR_MAP_SWIZZLE_128B);
    mk(3, d_in[6], 32, 576, 144, 9216, 64, 32, 24, 9, CU_TENSOR_MAP_SWIZZLE_64B);
    mk(4, d_in[4], 576, 4096, 1, 1152, 1152 * 4096, 144, 32, 1, CU_TENSOR_MAP_SWIZZLE_NONE);
    const int smem = SM_HEAD + NST * SLOT;
    cudaFuncSetAttribute(fused_kernel, cudaFuncAttributeMaxDynamicSharedMemorySize, smem);
    cudaFuncSetAttribute(fused_kernel, cudaFuncAttributePreferredSharedMemoryCarveout, cudaSharedmemCarveoutMaxShared);
    void* scr = nullptr;
    cudaGetSymbolAddress(&scr, g_scr);
    fused_kernel<<<NCTA, NTHR, smem, cudaStreamPerThread>>>(
        (const char*)d_in[3], (const char*)d_in[8], (const __nv_bfloat16*)d_in[0], (const __nv_bfloat16*)d_in[7], (const __nv_bfloat16*)d_in[9],
        (const __nv_bfloat16*)d_in[10], (__nv_bfloat16*)d_out, (Scratch*)scr, maps);
}
```
